```python
import torch

def _softmax(x, axis=-1):
    return torch.softmax(x, dim=axis)

def _gelu(x):
    return torch.nn.functional.gelu(x, approximate='tanh')

def _silu(x):
    return torch.nn.functional.silu(x)

def _sigmoid(x):
    return torch.sigmoid(x)

def _layernorm(x, axis=-1, eps=1e-05):
    m = x.mean(dim=axis, keepdim=True)
    v = x.var(dim=axis, keepdim=True, unbiased=False)
    return (x - m) / torch.sqrt(v + eps)

def _scatter_add(tgt, idx, src, axis=0):
    return tgt.clone().index_add_(axis, idx, src)

def _segment_sum(src, seg, n):
    out = torch.zeros((n,) + src.shape[1:], dtype=src.dtype)
    return out.index_add_(0, seg, src)

def _pad(x, pw):
    flat = tuple((v for pair in reversed(pw) for v in pair))
    return torch.nn.functional.pad(x, flat)
kernel_name = 'adaLN_cond__ssm_conv_h3__mixer_gmlp__prompt'

def setup_inputs():

    _w = lambda a: (lambda t: t.to(torch.bfloat16) if t.is_floating_point() else t)(torch.as_tensor(a))

    def _A_setup():
        B, S, D = (1, 2048, 640)
        ks = 4
        return {'q': _w((lambda *s: torch.randn(*s, dtype=torch.bfloat16) * 0.05)(B, S, D)), 'k': _w((lambda *s: torch.randn(*s, dtype=torch.bfloat16) * 1.6)(B, S, D)), 'v': _w((lambda *s: torch.randn(*s, dtype=torch.bfloat16) * 1.6)(B, S, D)), 'shift_k': _w((lambda *s: torch.randn(*s, dtype=torch.bfloat16) * 1.6)(D, ks) * 0.5), 'ssm_k': _w((lambda *s: torch.randn(*s, dtype=torch.bfloat16) * 1.6)(D, S) * (1.0 / S ** 0.5)), 'ssm_D': _w((lambda *s: torch.randn(*s, dtype=torch.bfloat16) * 1.6)(D))}
    _A_in = _A_setup()

    def _B_setup():
        B, S, D, F = (1, 2048, 640, 1728)
        Fh = F // 2
        return {'x': _w((lambda *s: torch.randn(*s, dtype=torch.bfloat16) * 0.05)(B, S, D)), 'w_in': _w((lambda *s: torch.randn(*s, dtype=torch.bfloat16) * 0.8)(D, 2 * Fh)), 'w_sp': _w(0.01 * (lambda *s: torch.randn(*s, dtype=torch.bfloat16) * 0.8)(S, S)), 'b_sp': _w(1.0 + 0.01 * (lambda *s: torch.randn(*s, dtype=torch.bfloat16) * 0.1)(S)), 'w_out': _w((lambda *s: torch.randn(*s, dtype=torch.bfloat16) * 0.1)(Fh, D))}
    _B_in = _B_setup()
    return {'A_q': _A_in['q'], 'A_k': _A_in['k'], 'A_v': _A_in['v'], 'A_shift_k': _A_in['shift_k'], 'A_ssm_k': _A_in['ssm_k'], 'A_ssm_D': _A_in['ssm_D'], 'B_x': _B_in['x'], 'B_w_in': _B_in['w_in'], 'B_w_sp': _B_in['w_sp'], 'B_b_sp': _B_in['b_sp'], 'B_w_out': _B_in['w_out'], 'c': _w((lambda *s: torch.randn(*s, dtype=torch.bfloat16) * 0.1)(1, 640) * 8.0), 'w_mod': _w((lambda *s: torch.randn(*s, dtype=torch.bfloat16) * 0.1)(640, 6 * 640) * 640 ** (-0.5) * 8.0)}

def reference(A_q, A_k, A_v, A_shift_k, A_ssm_k, A_ssm_D, B_x, B_w_in, B_w_sp, B_b_sp, B_w_out, c, w_mod):

    def _A_ref(q, k, v, shift_k, ssm_k, ssm_D):
        B, S, D = q.shape
        ks = shift_k.shape[-1]
        k_pad = _pad(k, ((0, 0), (ks - 1, 0), (0, 0)))
        k_shift = torch.zeros_like(k)
        for t in range(ks):
            k_shift = k_shift + k_pad[:, t:t + S, :] * shift_k[:, ks - 1 - t][None, None, :]
        kv = k_shift * v
        L = 2 * S
        kv_pad = _pad(kv, ((0, 0), (0, S), (0, 0)))
        kf_pad = _pad(ssm_k, ((0, 0), (0, S)))
        kv_f = (lambda x, axes=(-2, -1): torch.fft.rfft2(x.float(), dim=axes))(kv_pad[:, None, :, :], axes=(1, 2))
        kf_f = (lambda x, axes=(-2, -1): torch.fft.rfft2(x.float(), dim=axes))(kf_pad[:, None, :], axes=(1, 2))
        kf_f = (lambda x, *d: x.permute(*d))(kf_f, 1, 2, 0)
        y_f = kv_f * kf_f[None, :, :, :]
        y = (lambda x, s, axes=(-2, -1): torch.fft.irfft2(x, s=s, dim=axes).to(torch.bfloat16))(y_f, (1, L), axes=(1, 2))[:, 0, :S, :]
        y = y + kv * ssm_D[None, None, :]
        return q * y

    def _B_ref(x, w_in, w_sp, b_sp, w_out):
        B, S, D = x.shape
        F = w_in.shape[-1]
        Fh = F // 2
        z = _gelu(torch.einsum('bsd,df->bsf', x, w_in))
        z1 = z[..., :Fh].clone()
        z2 = _layernorm(z[..., Fh:], axis=-1)
        g = torch.einsum('ts,bsf->btf', w_sp, z2) + b_sp[None, :, None]
        return torch.einsum('bsf,fd->bsd', z1 * g, w_out)
    x = A_q
    mod = (_silu(c) @ w_mod).reshape(c.shape[0], 6, 1, -1)
    sa, ca, ga, sb, cb, gb = (mod[:, 0].clone(), mod[:, 1].clone(), mod[:, 2].clone(), mod[:, 3].clone(), mod[:, 4].clone(), mod[:, 5].clone())
    h = _layernorm(x, axis=-1) * (1 + ca) + sa
    x = x + ga * _A_ref(h, A_k, A_v, A_shift_k, A_ssm_k, A_ssm_D)
    h = _layernorm(x, axis=-1) * (1 + cb) + sb
    x = x + gb * _B_ref(h, B_w_in, B_w_sp, B_b_sp, B_w_out)
    return x
```

```cpp
#include <cuda_runtime.h>
#include <cuda.h>
#include <cuda_bf16.h>
#include <stdint.h>

typedef uint16_t u16; typedef uint32_t u32; typedef unsigned long long u64;
#define DEV __device__ __forceinline__

struct Scratch {
  u32 ctr[1280];
  u16 mod[4096];
  u64 stz[32 * 8 * 64];
  u16 u[640 * 2048];
  u16 y[32 * 640 * 64];
  u16 h2[32 * 80 * 8 * 64];
  u16 x1[32 * 80 * 8 * 64];
  u16 ws[2 * 4 * 80 * 11 * 64];
  u16 wo[4 * 108 * 20 * 64];
  u16 z2[32 * 4 * 8 * 27 * 64];
  u16 P[32 * 4 * 27 * 8 * 64];
};
__device__ __align__(1024) Scratch g_s;
enum { I_WS = 0, I_WO = 2, I_Z2 = 3 };
enum { S_U = 0, S_Y = 5, S_MOD = 6 };

struct Maps { CUtensorMap k, v, ssm, wmod, q, win, wsp, y, win32; };
struct Params {
  Scratch* s;
  const u16 *shk, *ssmD, *c, *wsp, *bsp, *wout;
  u16* out;
};

constexpr u32 sb = 1024;
constexpr u32 BT = 27648, XR = 5 * BT, AR = 6 * BT, MISC = XR + 81920, SMEM_BYTES = 232448;
constexpr u32 M_LN = MISC, M_BAR = MISC + 2048, M_MOD = M_BAR + 768, M_ZS = M_MOD + 7680, M_SM = M_ZS + 256, M_PROF = M_SM + 256;
constexpr u32 M_SC = M_MOD;
constexpr u32 US = XR, UP = 4224, PWB = US + 5 * UP, PWP = 4192, YR = 2 * BT, KP = 8320, KO = 4144, WM = YR + 41984;
constexpr u32 KVP = 8576, VO = 4480, SHK = 5 * KVP, YS = XR - 20480, QS = XR + 55296, WOST = 15360;
DEV u32 kslot(int j) { return YR + 128 + j * KP; }
enum { B_SS = 0, B_WM = 5, B_XF = 10, B_RF = 20, B_YD = 23, B_FULL = 25, B_PV = 31, B_WF = 34, B_WE = 41,
       B_VAL = 48, B_ZS = 54, B_KV = 56, B_EMPTY = 61, B_KB = 67,
       B_HD = 73, B_ZP = 74, B_PD = 75, B_Z2D = 76, B_Q = 77, B_UV = 78 };

DEV constexpr u32 bar(int i) { return sb + M_BAR + 8 * i; }

#define PROF(cond, i)
#define PROFD(cond, i, dep)
#define PROFV(cond, i, v)

DEV u32 smem_u32(const void* p) { return (u32)__cvta_generic_to_shared(p); }
DEV void wg_fence() { asm volatile("wgmma.fence.sync.aligned;" ::: "memory"); }
DEV void wg_commit() { asm volatile("wgmma.commit_group.sync.aligned;" ::: "memory"); }
template <int N> DEV void wg_wait() { asm volatile("wgmma.wait_group.sync.aligned %0;" ::"n"(N) : "memory"); }
DEV u64 desc_join(u32 lo, u32 hi) { return ((u64)hi << 32) | lo; }
DEV constexpr u32 desc_lo(u32 addr, u32 lbo) { return ((addr & 0x3FFFF) >> 4) | ((lbo >> 4) << 16); }
DEV void mbar_init(u32 bar, int cnt) { asm volatile("mbarrier.init.shared::cta.b64 [%0], %1;" ::"r"(bar), "r"(cnt) : "memory"); }
DEV void mbar_arrive(u32 bar) { asm volatile("mbarrier.arrive.shared::cta.b64 _, [%0];" ::"r"(bar) : "memory"); }
DEV void mbar_arrive_if(u32 bar, bool c) { asm volatile("{\n.reg .pred p;\nsetp.ne.u32 p, %1, 0;\n@p mbarrier.arrive.shared::cta.b64 _, [%0];\n}\n" ::"r"(bar), "r"((u32)c) : "memory"); }
DEV void mbar_wait(u32 bar, u32 parity) {
  asm volatile("{\n.reg .pred p, q;\n.reg .u32 n;\nmov.u32 n, 0;\nW_LOOP:\nmbarrier.try_wait.parity.shared::cta.b64 p, [%0], %1;\n"
               "add.u32 n, n, 4;\nsetp.gt.u32 q, n, 4194304;\n@q st.shared.u32 [n], n;\n@!p bra W_LOOP;\n}\n" ::"r"(bar), "r"(parity) : "memory");
}
DEV bool mbar_test(u32 bar, u32 parity) {
  u32 ok;
  asm volatile("{\n.reg .pred p;\nmbarrier.test_wait.parity.shared::cta.b64 p, [%1], %2;\nselp.u32 %0, 1, 0, p;\n}\n" : "=r"(ok) : "r"(bar), "r"(parity) : "memory");
  return ok;
}
DEV void trap_if_gt(int n, int lim) { asm volatile("{\n.reg .pred p;\nsetp.gt.s32 p, %0, %1;\n@p st.shared.u32 [%2], %0;\n}\n" ::"r"(n), "r"(lim), "r"(0x400000) : "memory"); }
DEV void until(u32 t0, int c) { while ((int)(clock() - t0) < c) {} }
DEV void bsync(int id, int n) { asm volatile("bar.sync %0, %1;" ::"r"(id), "r"(n) : "memory"); }
DEV bool bsync_and(int id, int n, bool v) {
  u32 r;
  asm volatile("{\n.reg .pred p, q;\nsetp.ne.u32 p, %3, 0;\nbarrier.red.and.aligned.pred q, %1, %2, p;\nselp.u32 %0, 1, 0, q;\n}\n" : "=r"(r) : "r"(id), "r"(n), "r"((u32)v) : "memory");
  return r;
}
DEV void barrive(int id, int n) { asm volatile("bar.arrive %0, %1;" ::"r"(id), "r"(n) : "memory"); }
DEV void fence_async_smem() { asm volatile("fence.proxy.async.shared::cta;" ::: "memory"); }
DEV void fence_gpu() { asm volatile("fence.acq_rel.gpu;" ::: "memory"); }
#define ELECT "{\n.reg .pred p;\nelect.sync _|p, 0xffffffff;\n"
DEV void e_init(u32 bar, int cnt) { asm volatile(ELECT "@p mbarrier.init.shared::cta.b64 [%0], %1;\n}\n" ::"r"(bar), "r"(cnt) : "memory"); }
DEV void e_init6(u32 b, int cnt) {
  asm volatile(ELECT "@p mbarrier.init.shared::cta.b64 [%0], 1;\n@p mbarrier.init.shared::cta.b64 [%0+96], 1;\n@p mbarrier.init.shared::cta.b64 [%0+192], 1;\n"
               "@p mbarrier.init.shared::cta.b64 [%0+288], 1;\n@p mbarrier.init.shared::cta.b64 [%0+480], 2;\n@p mbarrier.init.shared::cta.b64 [%0+576], %1;\n}\n" ::"r"(b), "r"(cnt) : "memory");
}
DEV void e_expect(u32 bar, u32 bytes) { asm volatile(ELECT "@p mbarrier.arrive.expect_tx.shared::cta.b64 _, [%0], %1;\n}\n" ::"r"(bar), "r"(bytes) : "memory"); }
DEV void e_arrive(u32 bar) { asm volatile(ELECT "@p mbarrier.arrive.shared::cta.b64 _, [%0];\n}\n" ::"r"(bar) : "memory"); }
DEV void e_load(u32 dst, const void* src, u32 bytes, u32 bar) {
  asm volatile(ELECT "@p cp.async.bulk.shared::cluster.global.mbarrier::complete_tx::bytes [%0], [%1], %2, [%3];\n}\n" ::"r"(dst), "l"(src), "r"(bytes), "r"(bar) : "memory");
}
DEV void e_xload(u32 dst, const void* src, u32 bytes, u32 bar) {
  asm volatile(ELECT "@p mbarrier.arrive.expect_tx.shared::cta.b64 _, [%3], %2;\n@p cp.async.bulk.shared::cluster.global.mbarrier::complete_tx::bytes [%0], [%1], %2, [%3];\n}\n"
               ::"r"(dst), "l"(src), "r"(bytes), "r"(bar) : "memory");
}
DEV void e_tma2d(u32 dst, const void* tm, u32 bar, int c0, int c1) {
  asm volatile(ELECT "@p cp.async.bulk.tensor.2d.shared::cluster.global.mbarrier::complete_tx::bytes [%0], [%1, {%3, %4}], [%2];\n}\n" ::"r"(dst), "l"(tm), "r"(bar), "r"(c0), "r"(c1) : "memory");
}
DEV void e_tma3d(u32 dst, const void* tm, u32 bar, int c0, int c1) {
  asm volatile(ELECT "@p cp.async.bulk.tensor.3d.shared::cluster.global.mbarrier::complete_tx::bytes [%0], [%1, {%3, %4, %5}], [%2];\n}\n" ::"r"(dst), "l"(tm), "r"(bar), "r"(c0), "r"(c1), "r"(0) : "memory");
}
DEV void e_pf3d(const void* tm, int c0, int c1) {
  asm volatile(ELECT "@p cp.async.bulk.prefetch.tensor.3d.L2.global [%0, {%1, %2, %3}];\n}\n" ::"l"(tm), "r"(c0), "r"(c1), "r"(0) : "memory");
}
DEV void load1d(u32 dst, const void* src, u32 bytes, u32 bar) {
  asm volatile("cp.async.bulk.shared::cluster.global.mbarrier::complete_tx::bytes [%0], [%1], %2, [%3];" ::"r"(dst), "l"(src), "r"(bytes), "r"(bar) : "memory");
}
DEV void pf2d(const void* tm, int c0, int c1) { asm volatile("cp.async.bulk.prefetch.tensor.2d.L2.global [%0, {%1, %2}];" ::"l"(tm), "r"(c0), "r"(c1) : "memory"); }
DEV void xtma2d(u32 dst, const void* tm, u32 bar, int c0, int c1, u32 bytes) {
  asm volatile("mbarrier.arrive.expect_tx.shared::cta.b64 _, [%2], %5;\ncp.async.bulk.tensor.2d.shared::cluster.global.mbarrier::complete_tx::bytes [%0], [%1, {%3, %4}], [%2];"
               ::"r"(dst), "l"(tm), "r"(bar), "r"(c0), "r"(c1), "r"(bytes) : "memory");
}
DEV void xload(u32 dst, const void* src, u32 bytes, u32 bar) {
  asm volatile("mbarrier.arrive.expect_tx.shared::cta.b64 _, [%3], %2;\ncp.async.bulk.shared::cluster.global.mbarrier::complete_tx::bytes [%0], [%1], %2, [%3];"
               ::"r"(dst), "l"(src), "r"(bytes), "r"(bar) : "memory");
}
DEV void e_prefetch(const void* src, u32 bytes) { asm volatile(ELECT "@p cp.async.bulk.prefetch.L2.global [%0], %1;\n}\n" ::"l"(src), "r"(bytes) : "memory"); }
DEV void e_tmpf(const void* tm) { asm volatile(ELECT "@p prefetch.tensormap [%0];\n}\n" ::"l"(tm) : "memory"); }
DEV uint4 ld_nc(const void* p) { uint4 v; asm volatile("ld.global.nc.v4.u32 {%0,%1,%2,%3}, [%4];" : "=r"(v.x), "=r"(v.y), "=r"(v.z), "=r"(v.w) : "l"(p)); return v; }
DEV void ldg128(u32* v, const void* p) { asm volatile("ld.global.cg.v4.u32 {%0,%1,%2,%3}, [%4];" : "=r"(v[0]), "=r"(v[1]), "=r"(v[2]), "=r"(v[3]) : "l"(p) : "memory"); }
DEV uint2 ld_rlx64(const void* p) { u64 a; asm volatile("ld.relaxed.gpu.global.b64 %0, [%1];" : "=l"(a) : "l"(p) : "memory"); return make_uint2((u32)a, (u32)(a >> 32)); }
DEV void cp16(u32 dst, const void* src) { asm volatile("cp.async.cg.shared.global [%0], [%1], 16;" ::"r"(dst), "l"(src) : "memory"); }
DEV void cp_wait() { asm volatile("cp.async.wait_all;" ::: "memory"); }
DEV void bulk_store(void* dst, u32 src, u32 bytes) {
  asm volatile("cp.async.bulk.global.shared::cta.bulk_group [%0], [%1], %2;\ncp.async.bulk.commit_group;" ::"l"(dst), "r"(src), "r"(bytes) : "memory");
}
DEV void bulk_wait() { asm volatile("cp.async.bulk.wait_group 0;" ::: "memory"); }
DEV u32 ld_rlx32(const void* p) { u32 a; asm volatile("ld.relaxed.gpu.global.u32 %0, [%1];" : "=r"(a) : "l"(p) : "memory"); return a; }
DEV void ctr_arrive(u32* ctr, int f, u32 ep, u32 sel) {
  asm volatile("{\n.reg .pred p;\nsetp.eq.u32 p, %2, 0;\n@p red.relaxed.gpu.global.add.u32 [%0], %1;\n}\n"
               ::"l"(ctr + 1 + sel), "r"((1u - 2u * (ep & 1)) << (8 * f)), "r"(sel) : "memory");
}
DEV void ctr_poll(u32* ctr, int f, u32 ep, u32 n) {
  const u32 want = (ep & 1) ? 0 : n;
  int it = 0;
#pragma unroll 1
  while (__any_sync(0xffffffffu, ((ld_rlx32(ctr + 1) >> (8 * f)) & 255) != want)) trap_if_gt(++it, 1 << 20);
}
DEV void stamp_post(u32* ctr, int i, u32 t0, u32 sel) {
  asm volatile("{\n.reg .pred p;\nsetp.eq.u32 p, %2, 0;\n@p red.relaxed.gpu.global.max.u32 [%0+4], %1;\n@p red.relaxed.gpu.global.add.u32 [%0], 1;\n}\n"
               ::"l"(ctr + 2 + 2 * i + sel), "r"((u32)clock() - t0), "r"(sel) : "memory");
}
DEV int stamp_wait(u32* ctr, int i, uint2 v = make_uint2(0, 0)) {
  int it = 0;
#pragma unroll 1
  while (__any_sync(0xffffffffu, v.x != 128)) { v = ld_rlx64(ctr + 2 + 2 * i); trap_if_gt(++it, 1 << 20); }
  return v.y;
}
DEV void tile_post(u32* w, u32 t0, u32 ep, bool c) { if (c) asm volatile("st.relaxed.gpu.global.u32 [%0], %1;" ::"l"(w), "r"(min((u32)clock() - t0, 0xfffffu) ^ ((ep + 1) << 20)) : "memory"); }
DEV int tile_wait(const u32* w, u32 ep) {
  u32 m;
  int it = 0;
#pragma unroll 1
  do {
    const uint2 a = ld_rlx64(w), b = ld_rlx64(w + 2);
    const u32 e = (ep + 1) << 20;
    m = max(max(a.x ^ e, a.y ^ e), max(b.x ^ e, b.y ^ e));
    trap_if_gt(++it, 1 << 20);
  } while (__any_sync(0xffffffffu, m >> 20));
  return m;
}
DEV void stg128(void* p, uint4 v) { asm volatile("st.global.v4.b32 [%0], {%1,%2,%3,%4};" ::"l"(p), "r"(v.x), "r"(v.y), "r"(v.z), "r"(v.w) : "memory"); }
DEV void stg32(void* p, u32 v) { asm volatile("st.global.b32 [%0], %1;" ::"l"(p), "r"(v) : "memory"); }
DEV u32 lds32(u32 a) { u32 v; asm volatile("ld.shared.b32 %0, [%1];" : "=r"(v) : "r"(a) : "memory"); return v; }
DEV void lds64(u32* v, u32 a) { asm volatile("ld.shared.v2.b32 {%0,%1}, [%2];" : "=r"(v[0]), "=r"(v[1]) : "r"(a) : "memory"); }
DEV uint4 lds128(u32 a) { uint4 v; asm volatile("ld.shared.v4.b32 {%0,%1,%2,%3}, [%4];" : "=r"(v.x), "=r"(v.y), "=r"(v.z), "=r"(v.w) : "r"(a) : "memory"); return v; }
DEV void lds128(u32* v, u32 a) { asm volatile("ld.shared.v4.b32 {%0,%1,%2,%3}, [%4];" : "=r"(v[0]), "=r"(v[1]), "=r"(v[2]), "=r"(v[3]) : "r"(a) : "memory"); }
DEV void sts16(u32 a, u32 v) { asm volatile("st.shared.b16 [%0], %1;" ::"r"(a), "h"((u16)v) : "memory"); }
DEV void sts32(u32 a, u32 v) { asm volatile("st.shared.b32 [%0], %1;" ::"r"(a), "r"(v) : "memory"); }
DEV void sts64f(u32 a, float x, float y) { asm volatile("st.shared.v2.f32 [%0], {%1,%2};" ::"r"(a), "f"(x), "f"(y) : "memory"); }
DEV void sts128(u32 a, uint4 v) { asm volatile("st.shared.v4.b32 [%0], {%1,%2,%3,%4};" ::"r"(a), "r"(v.x), "r"(v.y), "r"(v.z), "r"(v.w) : "memory"); }
DEV void consume(u32 x) { asm volatile("{\n.reg .pred p;\nsetp.eq.u32 p, %0, 0x7fc12345;\n@p nanosleep.u32 0;\n}\n" ::"r"(x) : "memory"); }
DEV int lane_now() { int l; asm volatile("mov.u32 %0, %%laneid;" : "=r"(l)); return l; }
DEV u32 opaque(u32 x) { asm volatile("" : "+r"(x)); return x; }
DEV void ldsm4(u32* r, u32 a) { asm volatile("ldmatrix.sync.aligned.m8n8.x4.shared.b16 {%0,%1,%2,%3}, [%4];" : "=r"(r[0]), "=r"(r[1]), "=r"(r[2]), "=r"(r[3]) : "r"(a) : "memory"); }
DEV void ldsm4t(u32* r, u32 a) { asm volatile("ldmatrix.sync.aligned.m8n8.x4.trans.shared.b16 {%0,%1,%2,%3}, [%4];" : "=r"(r[0]), "=r"(r[1]), "=r"(r[2]), "=r"(r[3]) : "r"(a) : "memory"); }
DEV void stsm4(u32 a, const u32* r) { asm volatile("stmatrix.sync.aligned.m8n8.x4.shared.b16 [%0], {%1,%2,%3,%4};" ::"r"(a), "r"(r[0]), "r"(r[1]), "r"(r[2]), "r"(r[3]) : "memory"); }
DEV void stsm4t(u32 a, const u32* r) { asm volatile("stmatrix.sync.aligned.m8n8.x4.trans.shared.b16 [%0], {%1,%2,%3,%4};" ::"r"(a), "r"(r[0]), "r"(r[1]), "r"(r[2]), "r"(r[3]) : "memory"); }
DEV void stsm2(u32 a, u32 r0, u32 r1) { asm volatile("stmatrix.sync.aligned.m8n8.x2.shared.b16 [%0], {%1,%2};" ::"r"(a), "r"(r0), "r"(r1) : "memory"); }
DEV void mma16816(float* c, u32 a0, u32 a1, u32 a2, u32 a3, u32 b0, u32 b1) {
  asm volatile("mma.sync.aligned.m16n8k16.row.col.f32.bf16.bf16.f32 {%0,%1,%2,%3}, {%4,%5,%6,%7}, {%8,%9}, {%0,%1,%2,%3};"
      : "+f"(c[0]), "+f"(c[1]), "+f"(c[2]), "+f"(c[3]) : "r"(a0), "r"(a1), "r"(a2), "r"(a3), "r"(b0), "r"(b1));
}
constexpr u32 ONE2 = 0x3f803f80u;
DEV u32 prmt(u32 a, u32 b, u32 s) { u32 r; asm("prmt.b32 %0, %1, %2, %3;" : "=r"(r) : "r"(a), "r"(b), "r"(s)); return r; }
DEV u32 hmul2(u32 a, u32 b) { u32 r; asm("mul.rn.bf16x2 %0, %1, %2;" : "=r"(r) : "r"(a), "r"(b)); return r; }
DEV u32 hadd2(u32 a, u32 b) { u32 r; asm("add.rn.bf16x2 %0, %1, %2;" : "=r"(r) : "r"(a), "r"(b)); return r; }
DEV u32 hfma2(u32 a, u32 b, u32 c) { u32 r; asm("fma.rn.bf16x2 %0, %1, %2, %3;" : "=r"(r) : "r"(a), "r"(b), "r"(c)); return r; }
DEV void row_stats(float (*c)[4], const u32* x) {
  mma16816(c[0], x[0], x[1], x[2], x[3], ONE2, ONE2);
  mma16816(c[1], x[0], x[1], x[2], x[3], x[0], x[2]);
  mma16816(c[2], x[0], x[1], x[2], x[3], x[1], x[3]);
}
DEV u32 pack2(float lo, float hi) { u32 r; asm("cvt.rn.bf16x2.f32 %0, %1, %2;" : "=r"(r) : "f"(hi), "f"(lo)); return r; }
DEV float bflo(u32 w) { return __uint_as_float(w * 65536u); }
DEV float bfhi(u32 w) { return __uint_as_float(w & 0xffff0000u); }
DEV u32 tagw(u32 w, u32 m, u32 par) { return (w & ~m) | (par & m); }
DEV u32 nz(u32 w) { return max(w, 1u); }
DEV float tanh_fast(float x) { float r; asm("tanh.approx.f32 %0, %1;" : "=f"(r) : "f"(x)); return r; }
DEV float shx(float v, int m) { return __shfl_xor_sync(0xffffffffu, v, m); }
DEV void wgmma_ss_128(float* d, u64 da, u64 db, int sd) {
  asm volatile("{\n.reg .pred p;\nsetp.ne.b32 p, %66, 0;\nwgmma.mma_async.sync.aligned.m64n128k16.f32.bf16.bf16 {%0, %1, %2, %3, %4, %5, %6, %7, %8, %9, %10, %11, %12, %13, %14, %15, %16, %17, %18, %19, %20, %21, %22, %23, %24, %25, %26, %27, %28, %29, %30, %31, %32, %33, %34, %35, %36, %37, %38, %39, %40, %41, %42, %43, %44, %45, %46, %47, %48, %49, %50, %51, %52, %53, %54, %55, %56, %57, %58, %59, %60, %61, %62, %63}, %64, %65, p, 1, 1, 0, 1;\n}\n"
    : "+f"(d[0]), "+f"(d[1]), "+f"(d[2]), "+f"(d[3]), "+f"(d[4]), "+f"(d[5]), "+f"(d[6]), "+f"(d[7]), "+f"(d[8]), "+f"(d[9]), "+f"(d[10]), "+f"(d[11]), "+f"(d[12]), "+f"(d[13]), "+f"(d[14]), "+f"(d[15]), "+f"(d[16]), "+f"(d[17]), "+f"(d[18]), "+f"(d[19]), "+f"(d[20]), "+f"(d[21]), "+f"(d[22]), "+f"(d[23]), "+f"(d[24]), "+f"(d[25]), "+f"(d[26]), "+f"(d[27]), "+f"(d[28]), "+f"(d[29]), "+f"(d[30]), "+f"(d[31]), "+f"(d[32]), "+f"(d[33]), "+f"(d[34]), "+f"(d[35]), "+f"(d[36]), "+f"(d[37]), "+f"(d[38]), "+f"(d[39]), "+f"(d[40]), "+f"(d[41]), "+f"(d[42]), "+f"(d[43]), "+f"(d[44]), "+f"(d[45]), "+f"(d[46]), "+f"(d[47]), "+f"(d[48]), "+f"(d[49]), "+f"(d[50]), "+f"(d[51]), "+f"(d[52]), "+f"(d[53]), "+f"(d[54]), "+f"(d[55]), "+f"(d[56]), "+f"(d[57]), "+f"(d[58]), "+f"(d[59]), "+f"(d[60]), "+f"(d[61]), "+f"(d[62]), "+f"(d[63]) : "l"(da), "l"(db), "r"(sd));
}
DEV void wgmma_ss_88(float* d, u64 da, u64 db, int sd) {
  asm volatile("{\n.reg .pred p;\nsetp.ne.b32 p, %46, 0;\nwgmma.mma_async.sync.aligned.m64n88k16.f32.bf16.bf16 {%0, %1, %2, %3, %4, %5, %6, %7, %8, %9, %10, %11, %12, %13, %14, %15, %16, %17, %18, %19, %20, %21, %22, %23, %24, %25, %26, %27, %28, %29, %30, %31, %32, %33, %34, %35, %36, %37, %38, %39, %40, %41, %42, %43}, %44, %45, p, 1, 1, 0, 1;\n}\n"
    : "+f"(d[0]), "+f"(d[1]), "+f"(d[2]), "+f"(d[3]), "+f"(d[4]), "+f"(d[5]), "+f"(d[6]), "+f"(d[7]), "+f"(d[8]), "+f"(d[9]), "+f"(d[10]), "+f"(d[11]), "+f"(d[12]), "+f"(d[13]), "+f"(d[14]), "+f"(d[15]), "+f"(d[16]), "+f"(d[17]), "+f"(d[18]), "+f"(d[19]), "+f"(d[20]), "+f"(d[21]), "+f"(d[22]), "+f"(d[23]), "+f"(d[24]), "+f"(d[25]), "+f"(d[26]), "+f"(d[27]), "+f"(d[28]), "+f"(d[29]), "+f"(d[30]), "+f"(d[31]), "+f"(d[32]), "+f"(d[33]), "+f"(d[34]), "+f"(d[35]), "+f"(d[36]), "+f"(d[37]), "+f"(d[38]), "+f"(d[39]), "+f"(d[40]), "+f"(d[41]), "+f"(d[42]), "+f"(d[43]) : "l"(da), "l"(db), "r"(sd));
}
DEV void wgmma_ss_160(float* d, u64 da, u64 db, int sd) {
  asm volatile("{\n.reg .pred p;\nsetp.ne.b32 p, %82, 0;\nwgmma.mma_async.sync.aligned.m64n160k16.f32.bf16.bf16 {%0, %1, %2, %3, %4, %5, %6, %7, %8, %9, %10, %11, %12, %13, %14, %15, %16, %17, %18, %19, %20, %21, %22, %23, %24, %25, %26, %27, %28, %29, %30, %31, %32, %33, %34, %35, %36, %37, %38, %39, %40, %41, %42, %43, %44, %45, %46, %47, %48, %49, %50, %51, %52, %53, %54, %55, %56, %57, %58, %59, %60, %61, %62, %63, %64, %65, %66, %67, %68, %69, %70, %71, %72, %73, %74, %75, %76, %77, %78, %79}, %80, %81, p, 1, 1, 0, 1;\n}\n"
    : "+f"(d[0]), "+f"(d[1]), "+f"(d[2]), "+f"(d[3]), "+f"(d[4]), "+f"(d[5]), "+f"(d[6]), "+f"(d[7]), "+f"(d[8]), "+f"(d[9]), "+f"(d[10]), "+f"(d[11]), "+f"(d[12]), "+f"(d[13]), "+f"(d[14]), "+f"(d[15]), "+f"(d[16]), "+f"(d[17]), "+f"(d[18]), "+f"(d[19]), "+f"(d[20]), "+f"(d[21]), "+f"(d[22]), "+f"(d[23]), "+f"(d[24]), "+f"(d[25]), "+f"(d[26]), "+f"(d[27]), "+f"(d[28]), "+f"(d[29]), "+f"(d[30]), "+f"(d[31]), "+f"(d[32]), "+f"(d[33]), "+f"(d[34]), "+f"(d[35]), "+f"(d[36]), "+f"(d[37]), "+f"(d[38]), "+f"(d[39]), "+f"(d[40]), "+f"(d[41]), "+f"(d[42]), "+f"(d[43]), "+f"(d[44]), "+f"(d[45]), "+f"(d[46]), "+f"(d[47]), "+f"(d[48]), "+f"(d[49]), "+f"(d[50]), "+f"(d[51]), "+f"(d[52]), "+f"(d[53]), "+f"(d[54]), "+f"(d[55]), "+f"(d[56]), "+f"(d[57]), "+f"(d[58]), "+f"(d[59]), "+f"(d[60]), "+f"(d[61]), "+f"(d[62]), "+f"(d[63]), "+f"(d[64]), "+f"(d[65]), "+f"(d[66]), "+f"(d[67]), "+f"(d[68]), "+f"(d[69]), "+f"(d[70]), "+f"(d[71]), "+f"(d[72]), "+f"(d[73]), "+f"(d[74]), "+f"(d[75]), "+f"(d[76]), "+f"(d[77]), "+f"(d[78]), "+f"(d[79]) : "l"(da), "l"(db), "r"(sd));
}
template <int N> DEV void wgmma_rs(float* d, const u32* a, u64 db);
template <> DEV void wgmma_rs<256>(float* d, const u32* a, u64 db) {
  asm volatile("wgmma.mma_async.sync.aligned.m64n256k16.f32.bf16.bf16 {%0, %1, %2, %3, %4, %5, %6, %7, %8, %9, %10, %11, %12, %13, %14, %15, %16, %17, %18, %19, %20, %21, %22, %23, %24, %25, %26, %27, %28, %29, %30, %31, %32, %33, %34, %35, %36, %37, %38, %39, %40, %41, %42, %43, %44, %45, %46, %47, %48, %49, %50, %51, %52, %53, %54, %55, %56, %57, %58, %59, %60, %61, %62, %63, %64, %65, %66, %67, %68, %69, %70, %71, %72, %73, %74, %75, %76, %77, %78, %79, %80, %81, %82, %83, %84, %85, %86, %87, %88, %89, %90, %91, %92, %93, %94, %95, %96, %97, %98, %99, %100, %101, %102, %103, %104, %105, %106, %107, %108, %109, %110, %111, %112, %113, %114, %115, %116, %117, %118, %119, %120, %121, %122, %123, %124, %125, %126, %127}, {%128, %129, %130, %131}, %132, 0, 1, 1, 0;"
    : "+f"(d[0]), "+f"(d[1]), "+f"(d[2]), "+f"(d[3]), "+f"(d[4]), "+f"(d[5]), "+f"(d[6]), "+f"(d[7]), "+f"(d[8]), "+f"(d[9]), "+f"(d[10]), "+f"(d[11]), "+f"(d[12]), "+f"(d[13]), "+f"(d[14]), "+f"(d[15]), "+f"(d[16]), "+f"(d[17]), "+f"(d[18]), "+f"(d[19]), "+f"(d[20]), "+f"(d[21]), "+f"(d[22]), "+f"(d[23]), "+f"(d[24]), "+f"(d[25]), "+f"(d[26]), "+f"(d[27]), "+f"(d[28]), "+f"(d[29]), "+f"(d[30]), "+f"(d[31]), "+f"(d[32]), "+f"(d[33]), "+f"(d[34]), "+f"(d[35]), "+f"(d[36]), "+f"(d[37]), "+f"(d[38]), "+f"(d[39]), "+f"(d[40]), "+f"(d[41]), "+f"(d[42]), "+f"(d[43]), "+f"(d[44]), "+f"(d[45]), "+f"(d[46]), "+f"(d[47]), "+f"(d[48]), "+f"(d[49]), "+f"(d[50]), "+f"(d[51]), "+f"(d[52]), "+f"(d[53]), "+f"(d[54]), "+f"(d[55]), "+f"(d[56]), "+f"(d[57]), "+f"(d[58]), "+f"(d[59]), "+f"(d[60]), "+f"(d[61]), "+f"(d[62]), "+f"(d[63]), "+f"(d[64]), "+f"(d[65]), "+f"(d[66]), "+f"(d[67]), "+f"(d[68]), "+f"(d[69]), "+f"(d[70]), "+f"(d[71]), "+f"(d[72]), "+f"(d[73]), "+f"(d[74]), "+f"(d[75]), "+f"(d[76]), "+f"(d[77]), "+f"(d[78]), "+f"(d[79]), "+f"(d[80]), "+f"(d[81]), "+f"(d[82]), "+f"(d[83]), "+f"(d[84]), "+f"(d[85]), "+f"(d[86]), "+f"(d[87]), "+f"(d[88]), "+f"(d[89]), "+f"(d[90]), "+f"(d[91]), "+f"(d[92]), "+f"(d[93]), "+f"(d[94]), "+f"(d[95]), "+f"(d[96]), "+f"(d[97]), "+f"(d[98]), "+f"(d[99]), "+f"(d[100]), "+f"(d[101]), "+f"(d[102]), "+f"(d[103]), "+f"(d[104]), "+f"(d[105]), "+f"(d[106]), "+f"(d[107]), "+f"(d[108]), "+f"(d[109]), "+f"(d[110]), "+f"(d[111]), "+f"(d[112]), "+f"(d[113]), "+f"(d[114]), "+f"(d[115]), "+f"(d[116]), "+f"(d[117]), "+f"(d[118]), "+f"(d[119]), "+f"(d[120]), "+f"(d[121]), "+f"(d[122]), "+f"(d[123]), "+f"(d[124]), "+f"(d[125]), "+f"(d[126]), "+f"(d[127]) : "r"(a[0]), "r"(a[1]), "r"(a[2]), "r"(a[3]), "l"(db));
}
template <> DEV void wgmma_rs<240>(float* d, const u32* a, u64 db) {
  asm volatile("wgmma.mma_async.sync.aligned.m64n240k16.f32.bf16.bf16 {%0, %1, %2, %3, %4, %5, %6, %7, %8, %9, %10, %11, %12, %13, %14, %15, %16, %17, %18, %19, %20, %21, %22, %23, %24, %25, %26, %27, %28, %29, %30, %31, %32, %33, %34, %35, %36, %37, %38, %39, %40, %41, %42, %43, %44, %45, %46, %47, %48, %49, %50, %51, %52, %53, %54, %55, %56, %57, %58, %59, %60, %61, %62, %63, %64, %65, %66, %67, %68, %69, %70, %71, %72, %73, %74, %75, %76, %77, %78, %79, %80, %81, %82, %83, %84, %85, %86, %87, %88, %89, %90, %91, %92, %93, %94, %95, %96, %97, %98, %99, %100, %101, %102, %103, %104, %105, %106, %107, %108, %109, %110, %111, %112, %113, %114, %115, %116, %117, %118, %119}, {%120, %121, %122, %123}, %124, 1, 1, 1, 0;"
    : "+f"(d[0]), "+f"(d[1]), "+f"(d[2]), "+f"(d[3]), "+f"(d[4]), "+f"(d[5]), "+f"(d[6]), "+f"(d[7]), "+f"(d[8]), "+f"(d[9]), "+f"(d[10]), "+f"(d[11]), "+f"(d[12]), "+f"(d[13]), "+f"(d[14]), "+f"(d[15]), "+f"(d[16]), "+f"(d[17]), "+f"(d[18]), "+f"(d[19]), "+f"(d[20]), "+f"(d[21]), "+f"(d[22]), "+f"(d[23]), "+f"(d[24]), "+f"(d[25]), "+f"(d[26]), "+f"(d[27]), "+f"(d[28]), "+f"(d[29]), "+f"(d[30]), "+f"(d[31]), "+f"(d[32]), "+f"(d[33]), "+f"(d[34]), "+f"(d[35]), "+f"(d[36]), "+f"(d[37]), "+f"(d[38]), "+f"(d[39]), "+f"(d[40]), "+f"(d[41]), "+f"(d[42]), "+f"(d[43]), "+f"(d[44]), "+f"(d[45]), "+f"(d[46]), "+f"(d[47]), "+f"(d[48]), "+f"(d[49]), "+f"(d[50]), "+f"(d[51]), "+f"(d[52]), "+f"(d[53]), "+f"(d[54]), "+f"(d[55]), "+f"(d[56]), "+f"(d[57]), "+f"(d[58]), "+f"(d[59]), "+f"(d[60]), "+f"(d[61]), "+f"(d[62]), "+f"(d[63]), "+f"(d[64]), "+f"(d[65]), "+f"(d[66]), "+f"(d[67]), "+f"(d[68]), "+f"(d[69]), "+f"(d[70]), "+f"(d[71]), "+f"(d[72]), "+f"(d[73]), "+f"(d[74]), "+f"(d[75]), "+f"(d[76]), "+f"(d[77]), "+f"(d[78]), "+f"(d[79]), "+f"(d[80]), "+f"(d[81]), "+f"(d[82]), "+f"(d[83]), "+f"(d[84]), "+f"(d[85]), "+f"(d[86]), "+f"(d[87]), "+f"(d[88]), "+f"(d[89]), "+f"(d[90]), "+f"(d[91]), "+f"(d[92]), "+f"(d[93]), "+f"(d[94]), "+f"(d[95]), "+f"(d[96]), "+f"(d[97]), "+f"(d[98]), "+f"(d[99]), "+f"(d[100]), "+f"(d[101]), "+f"(d[102]), "+f"(d[103]), "+f"(d[104]), "+f"(d[105]), "+f"(d[106]), "+f"(d[107]), "+f"(d[108]), "+f"(d[109]), "+f"(d[110]), "+f"(d[111]), "+f"(d[112]), "+f"(d[113]), "+f"(d[114]), "+f"(d[115]), "+f"(d[116]), "+f"(d[117]), "+f"(d[118]), "+f"(d[119]) : "r"(a[0]), "r"(a[1]), "r"(a[2]), "r"(a[3]), "l"(db));
}
template <> DEV void wgmma_rs<224>(float* d, const u32* a, u64 db) {
  asm volatile("wgmma.mma_async.sync.aligned.m64n224k16.f32.bf16.bf16 {%0, %1, %2, %3, %4, %5, %6, %7, %8, %9, %10, %11, %12, %13, %14, %15, %16, %17, %18, %19, %20, %21, %22, %23, %24, %25, %26, %27, %28, %29, %30, %31, %32, %33, %34, %35, %36, %37, %38, %39, %40, %41, %42, %43, %44, %45, %46, %47, %48, %49, %50, %51, %52, %53, %54, %55, %56, %57, %58, %59, %60, %61, %62, %63, %64, %65, %66, %67, %68, %69, %70, %71, %72, %73, %74, %75, %76, %77, %78, %79, %80, %81, %82, %83, %84, %85, %86, %87, %88, %89, %90, %91, %92, %93, %94, %95, %96, %97, %98, %99, %100, %101, %102, %103, %104, %105, %106, %107, %108, %109, %110, %111}, {%112, %113, %114, %115}, %116, 1, 1, 1, 0;"
    : "+f"(d[0]), "+f"(d[1]), "+f"(d[2]), "+f"(d[3]), "+f"(d[4]), "+f"(d[5]), "+f"(d[6]), "+f"(d[7]), "+f"(d[8]), "+f"(d[9]), "+f"(d[10]), "+f"(d[11]), "+f"(d[12]), "+f"(d[13]), "+f"(d[14]), "+f"(d[15]), "+f"(d[16]), "+f"(d[17]), "+f"(d[18]), "+f"(d[19]), "+f"(d[20]), "+f"(d[21]), "+f"(d[22]), "+f"(d[23]), "+f"(d[24]), "+f"(d[25]), "+f"(d[26]), "+f"(d[27]), "+f"(d[28]), "+f"(d[29]), "+f"(d[30]), "+f"(d[31]), "+f"(d[32]), "+f"(d[33]), "+f"(d[34]), "+f"(d[35]), "+f"(d[36]), "+f"(d[37]), "+f"(d[38]), "+f"(d[39]), "+f"(d[40]), "+f"(d[41]), "+f"(d[42]), "+f"(d[43]), "+f"(d[44]), "+f"(d[45]), "+f"(d[46]), "+f"(d[47]), "+f"(d[48]), "+f"(d[49]), "+f"(d[50]), "+f"(d[51]), "+f"(d[52]), "+f"(d[53]), "+f"(d[54]), "+f"(d[55]), "+f"(d[56]), "+f"(d[57]), "+f"(d[58]), "+f"(d[59]), "+f"(d[60]), "+f"(d[61]), "+f"(d[62]), "+f"(d[63]), "+f"(d[64]), "+f"(d[65]), "+f"(d[66]), "+f"(d[67]), "+f"(d[68]), "+f"(d[69]), "+f"(d[70]), "+f"(d[71]), "+f"(d[72]), "+f"(d[73]), "+f"(d[74]), "+f"(d[75]), "+f"(d[76]), "+f"(d[77]), "+f"(d[78]), "+f"(d[79]), "+f"(d[80]), "+f"(d[81]), "+f"(d[82]), "+f"(d[83]), "+f"(d[84]), "+f"(d[85]), "+f"(d[86]), "+f"(d[87]), "+f"(d[88]), "+f"(d[89]), "+f"(d[90]), "+f"(d[91]), "+f"(d[92]), "+f"(d[93]), "+f"(d[94]), "+f"(d[95]), "+f"(d[96]), "+f"(d[97]), "+f"(d[98]), "+f"(d[99]), "+f"(d[100]), "+f"(d[101]), "+f"(d[102]), "+f"(d[103]), "+f"(d[104]), "+f"(d[105]), "+f"(d[106]), "+f"(d[107]), "+f"(d[108]), "+f"(d[109]), "+f"(d[110]), "+f"(d[111]) : "r"(a[0]), "r"(a[1]), "r"(a[2]), "r"(a[3]), "l"(db));
}
template <> DEV void wgmma_rs<208>(float* d, const u32* a, u64 db) {
  asm volatile("wgmma.mma_async.sync.aligned.m64n208k16.f32.bf16.bf16 {%0, %1, %2, %3, %4, %5, %6, %7, %8, %9, %10, %11, %12, %13, %14, %15, %16, %17, %18, %19, %20, %21, %22, %23, %24, %25, %26, %27, %28, %29, %30, %31, %32, %33, %34, %35, %36, %37, %38, %39, %40, %41, %42, %43, %44, %45, %46, %47, %48, %49, %50, %51, %52, %53, %54, %55, %56, %57, %58, %59, %60, %61, %62, %63, %64, %65, %66, %67, %68, %69, %70, %71, %72, %73, %74, %75, %76, %77, %78, %79, %80, %81, %82, %83, %84, %85, %86, %87, %88, %89, %90, %91, %92, %93, %94, %95, %96, %97, %98, %99, %100, %101, %102, %103}, {%104, %105, %106, %107}, %108, 1, 1, 1, 0;"
    : "+f"(d[0]), "+f"(d[1]), "+f"(d[2]), "+f"(d[3]), "+f"(d[4]), "+f"(d[5]), "+f"(d[6]), "+f"(d[7]), "+f"(d[8]), "+f"(d[9]), "+f"(d[10]), "+f"(d[11]), "+f"(d[12]), "+f"(d[13]), "+f"(d[14]), "+f"(d[15]), "+f"(d[16]), "+f"(d[17]), "+f"(d[18]), "+f"(d[19]), "+f"(d[20]), "+f"(d[21]), "+f"(d[22]), "+f"(d[23]), "+f"(d[24]), "+f"(d[25]), "+f"(d[26]), "+f"(d[27]), "+f"(d[28]), "+f"(d[29]), "+f"(d[30]), "+f"(d[31]), "+f"(d[32]), "+f"(d[33]), "+f"(d[34]), "+f"(d[35]), "+f"(d[36]), "+f"(d[37]), "+f"(d[38]), "+f"(d[39]), "+f"(d[40]), "+f"(d[41]), "+f"(d[42]), "+f"(d[43]), "+f"(d[44]), "+f"(d[45]), "+f"(d[46]), "+f"(d[47]), "+f"(d[48]), "+f"(d[49]), "+f"(d[50]), "+f"(d[51]), "+f"(d[52]), "+f"(d[53]), "+f"(d[54]), "+f"(d[55]), "+f"(d[56]), "+f"(d[57]), "+f"(d[58]), "+f"(d[59]), "+f"(d[60]), "+f"(d[61]), "+f"(d[62]), "+f"(d[63]), "+f"(d[64]), "+f"(d[65]), "+f"(d[66]), "+f"(d[67]), "+f"(d[68]), "+f"(d[69]), "+f"(d[70]), "+f"(d[71]), "+f"(d[72]), "+f"(d[73]), "+f"(d[74]), "+f"(d[75]), "+f"(d[76]), "+f"(d[77]), "+f"(d[78]), "+f"(d[79]), "+f"(d[80]), "+f"(d[81]), "+f"(d[82]), "+f"(d[83]), "+f"(d[84]), "+f"(d[85]), "+f"(d[86]), "+f"(d[87]), "+f"(d[88]), "+f"(d[89]), "+f"(d[90]), "+f"(d[91]), "+f"(d[92]), "+f"(d[93]), "+f"(d[94]), "+f"(d[95]), "+f"(d[96]), "+f"(d[97]), "+f"(d[98]), "+f"(d[99]), "+f"(d[100]), "+f"(d[101]), "+f"(d[102]), "+f"(d[103]) : "r"(a[0]), "r"(a[1]), "r"(a[2]), "r"(a[3]), "l"(db));
}
template <> DEV void wgmma_rs<192>(float* d, const u32* a, u64 db) {
  asm volatile("wgmma.mma_async.sync.aligned.m64n192k16.f32.bf16.bf16 {%0, %1, %2, %3, %4, %5, %6, %7, %8, %9, %10, %11, %12, %13, %14, %15, %16, %17, %18, %19, %20, %21, %22, %23, %24, %25, %26, %27, %28, %29, %30, %31, %32, %33, %34, %35, %36, %37, %38, %39, %40, %41, %42, %43, %44, %45, %46, %47, %48, %49, %50, %51, %52, %53, %54, %55, %56, %57, %58, %59, %60, %61, %62, %63, %64, %65, %66, %67, %68, %69, %70, %71, %72, %73, %74, %75, %76, %77, %78, %79, %80, %81, %82, %83, %84, %85, %86, %87, %88, %89, %90, %91, %92, %93, %94, %95}, {%96, %97, %98, %99}, %100, 1, 1, 1, 0;"
    : "+f"(d[0]), "+f"(d[1]), "+f"(d[2]), "+f"(d[3]), "+f"(d[4]), "+f"(d[5]), "+f"(d[6]), "+f"(d[7]), "+f"(d[8]), "+f"(d[9]), "+f"(d[10]), "+f"(d[11]), "+f"(d[12]), "+f"(d[13]), "+f"(d[14]), "+f"(d[15]), "+f"(d[16]), "+f"(d[17]), "+f"(d[18]), "+f"(d[19]), "+f"(d[20]), "+f"(d[21]), "+f"(d[22]), "+f"(d[23]), "+f"(d[24]), "+f"(d[25]), "+f"(d[26]), "+f"(d[27]), "+f"(d[28]), "+f"(d[29]), "+f"(d[30]), "+f"(d[31]), "+f"(d[32]), "+f"(d[33]), "+f"(d[34]), "+f"(d[35]), "+f"(d[36]), "+f"(d[37]), "+f"(d[38]), "+f"(d[39]), "+f"(d[40]), "+f"(d[41]), "+f"(d[42]), "+f"(d[43]), "+f"(d[44]), "+f"(d[45]), "+f"(d[46]), "+f"(d[47]), "+f"(d[48]), "+f"(d[49]), "+f"(d[50]), "+f"(d[51]), "+f"(d[52]), "+f"(d[53]), "+f"(d[54]), "+f"(d[55]), "+f"(d[56]), "+f"(d[57]), "+f"(d[58]), "+f"(d[59]), "+f"(d[60]), "+f"(d[61]), "+f"(d[62]), "+f"(d[63]), "+f"(d[64]), "+f"(d[65]), "+f"(d[66]), "+f"(d[67]), "+f"(d[68]), "+f"(d[69]), "+f"(d[70]), "+f"(d[71]), "+f"(d[72]), "+f"(d[73]), "+f"(d[74]), "+f"(d[75]), "+f"(d[76]), "+f"(d[77]), "+f"(d[78]), "+f"(d[79]), "+f"(d[80]), "+f"(d[81]), "+f"(d[82]), "+f"(d[83]), "+f"(d[84]), "+f"(d[85]), "+f"(d[86]), "+f"(d[87]), "+f"(d[88]), "+f"(d[89]), "+f"(d[90]), "+f"(d[91]), "+f"(d[92]), "+f"(d[93]), "+f"(d[94]), "+f"(d[95]) : "r"(a[0]), "r"(a[1]), "r"(a[2]), "r"(a[3]), "l"(db));
}
template <> DEV void wgmma_rs<176>(float* d, const u32* a, u64 db) {
  asm volatile("wgmma.mma_async.sync.aligned.m64n176k16.f32.bf16.bf16 {%0, %1, %2, %3, %4, %5, %6, %7, %8, %9, %10, %11, %12, %13, %14, %15, %16, %17, %18, %19, %20, %21, %22, %23, %24, %25, %26, %27, %28, %29, %30, %31, %32, %33, %34, %35, %36, %37, %38, %39, %40, %41, %42, %43, %44, %45, %46, %47, %48, %49, %50, %51, %52, %53, %54, %55, %56, %57, %58, %59, %60, %61, %62, %63, %64, %65, %66, %67, %68, %69, %70, %71, %72, %73, %74, %75, %76, %77, %78, %79, %80, %81, %82, %83, %84, %85, %86, %87}, {%88, %89, %90, %91}, %92, 1, 1, 1, 0;"
    : "+f"(d[0]), "+f"(d[1]), "+f"(d[2]), "+f"(d[3]), "+f"(d[4]), "+f"(d[5]), "+f"(d[6]), "+f"(d[7]), "+f"(d[8]), "+f"(d[9]), "+f"(d[10]), "+f"(d[11]), "+f"(d[12]), "+f"(d[13]), "+f"(d[14]), "+f"(d[15]), "+f"(d[16]), "+f"(d[17]), "+f"(d[18]), "+f"(d[19]), "+f"(d[20]), "+f"(d[21]), "+f"(d[22]), "+f"(d[23]), "+f"(d[24]), "+f"(d[25]), "+f"(d[26]), "+f"(d[27]), "+f"(d[28]), "+f"(d[29]), "+f"(d[30]), "+f"(d[31]), "+f"(d[32]), "+f"(d[33]), "+f"(d[34]), "+f"(d[35]), "+f"(d[36]), "+f"(d[37]), "+f"(d[38]), "+f"(d[39]), "+f"(d[40]), "+f"(d[41]), "+f"(d[42]), "+f"(d[43]), "+f"(d[44]), "+f"(d[45]), "+f"(d[46]), "+f"(d[47]), "+f"(d[48]), "+f"(d[49]), "+f"(d[50]), "+f"(d[51]), "+f"(d[52]), "+f"(d[53]), "+f"(d[54]), "+f"(d[55]), "+f"(d[56]), "+f"(d[57]), "+f"(d[58]), "+f"(d[59]), "+f"(d[60]), "+f"(d[61]), "+f"(d[62]), "+f"(d[63]), "+f"(d[64]), "+f"(d[65]), "+f"(d[66]), "+f"(d[67]), "+f"(d[68]), "+f"(d[69]), "+f"(d[70]), "+f"(d[71]), "+f"(d[72]), "+f"(d[73]), "+f"(d[74]), "+f"(d[75]), "+f"(d[76]), "+f"(d[77]), "+f"(d[78]), "+f"(d[79]), "+f"(d[80]), "+f"(d[81]), "+f"(d[82]), "+f"(d[83]), "+f"(d[84]), "+f"(d[85]), "+f"(d[86]), "+f"(d[87]) : "r"(a[0]), "r"(a[1]), "r"(a[2]), "r"(a[3]), "l"(db));
}
template <> DEV void wgmma_rs<160>(float* d, const u32* a, u64 db) {
  asm volatile("wgmma.mma_async.sync.aligned.m64n160k16.f32.bf16.bf16 {%0, %1, %2, %3, %4, %5, %6, %7, %8, %9, %10, %11, %12, %13, %14, %15, %16, %17, %18, %19, %20, %21, %22, %23, %24, %25, %26, %27, %28, %29, %30, %31, %32, %33, %34, %35, %36, %37, %38, %39, %40, %41, %42, %43, %44, %45, %46, %47, %48, %49, %50, %51, %52, %53, %54, %55, %56, %57, %58, %59, %60, %61, %62, %63, %64, %65, %66, %67, %68, %69, %70, %71, %72, %73, %74, %75, %76, %77, %78, %79}, {%80, %81, %82, %83}, %84, 1, 1, 1, 0;"
    : "+f"(d[0]), "+f"(d[1]), "+f"(d[2]), "+f"(d[3]), "+f"(d[4]), "+f"(d[5]), "+f"(d[6]), "+f"(d[7]), "+f"(d[8]), "+f"(d[9]), "+f"(d[10]), "+f"(d[11]), "+f"(d[12]), "+f"(d[13]), "+f"(d[14]), "+f"(d[15]), "+f"(d[16]), "+f"(d[17]), "+f"(d[18]), "+f"(d[19]), "+f"(d[20]), "+f"(d[21]), "+f"(d[22]), "+f"(d[23]), "+f"(d[24]), "+f"(d[25]), "+f"(d[26]), "+f"(d[27]), "+f"(d[28]), "+f"(d[29]), "+f"(d[30]), "+f"(d[31]), "+f"(d[32]), "+f"(d[33]), "+f"(d[34]), "+f"(d[35]), "+f"(d[36]), "+f"(d[37]), "+f"(d[38]), "+f"(d[39]), "+f"(d[40]), "+f"(d[41]), "+f"(d[42]), "+f"(d[43]), "+f"(d[44]), "+f"(d[45]), "+f"(d[46]), "+f"(d[47]), "+f"(d[48]), "+f"(d[49]), "+f"(d[50]), "+f"(d[51]), "+f"(d[52]), "+f"(d[53]), "+f"(d[54]), "+f"(d[55]), "+f"(d[56]), "+f"(d[57]), "+f"(d[58]), "+f"(d[59]), "+f"(d[60]), "+f"(d[61]), "+f"(d[62]), "+f"(d[63]), "+f"(d[64]), "+f"(d[65]), "+f"(d[66]), "+f"(d[67]), "+f"(d[68]), "+f"(d[69]), "+f"(d[70]), "+f"(d[71]), "+f"(d[72]), "+f"(d[73]), "+f"(d[74]), "+f"(d[75]), "+f"(d[76]), "+f"(d[77]), "+f"(d[78]), "+f"(d[79]) : "r"(a[0]), "r"(a[1]), "r"(a[2]), "r"(a[3]), "l"(db));
}
template <> DEV void wgmma_rs<144>(float* d, const u32* a, u64 db) {
  asm volatile("wgmma.mma_async.sync.aligned.m64n144k16.f32.bf16.bf16 {%0, %1, %2, %3, %4, %5, %6, %7, %8, %9, %10, %11, %12, %13, %14, %15, %16, %17, %18, %19, %20, %21, %22, %23, %24, %25, %26, %27, %28, %29, %30, %31, %32, %33, %34, %35, %36, %37, %38, %39, %40, %41, %42, %43, %44, %45, %46, %47, %48, %49, %50, %51, %52, %53, %54, %55, %56, %57, %58, %59, %60, %61, %62, %63, %64, %65, %66, %67, %68, %69, %70, %71}, {%72, %73, %74, %75}, %76, 1, 1, 1, 0;"
    : "+f"(d[0]), "+f"(d[1]), "+f"(d[2]), "+f"(d[3]), "+f"(d[4]), "+f"(d[5]), "+f"(d[6]), "+f"(d[7]), "+f"(d[8]), "+f"(d[9]), "+f"(d[10]), "+f"(d[11]), "+f"(d[12]), "+f"(d[13]), "+f"(d[14]), "+f"(d[15]), "+f"(d[16]), "+f"(d[17]), "+f"(d[18]), "+f"(d[19]), "+f"(d[20]), "+f"(d[21]), "+f"(d[22]), "+f"(d[23]), "+f"(d[24]), "+f"(d[25]), "+f"(d[26]), "+f"(d[27]), "+f"(d[28]), "+f"(d[29]), "+f"(d[30]), "+f"(d[31]), "+f"(d[32]), "+f"(d[33]), "+f"(d[34]), "+f"(d[35]), "+f"(d[36]), "+f"(d[37]), "+f"(d[38]), "+f"(d[39]), "+f"(d[40]), "+f"(d[41]), "+f"(d[42]), "+f"(d[43]), "+f"(d[44]), "+f"(d[45]), "+f"(d[46]), "+f"(d[47]), "+f"(d[48]), "+f"(d[49]), "+f"(d[50]), "+f"(d[51]), "+f"(d[52]), "+f"(d[53]), "+f"(d[54]), "+f"(d[55]), "+f"(d[56]), "+f"(d[57]), "+f"(d[58]), "+f"(d[59]), "+f"(d[60]), "+f"(d[61]), "+f"(d[62]), "+f"(d[63]), "+f"(d[64]), "+f"(d[65]), "+f"(d[66]), "+f"(d[67]), "+f"(d[68]), "+f"(d[69]), "+f"(d[70]), "+f"(d[71]) : "r"(a[0]), "r"(a[1]), "r"(a[2]), "r"(a[3]), "l"(db));
}
template <> DEV void wgmma_rs<128>(float* d, const u32* a, u64 db) {
  asm volatile("wgmma.mma_async.sync.aligned.m64n128k16.f32.bf16.bf16 {%0, %1, %2, %3, %4, %5, %6, %7, %8, %9, %10, %11, %12, %13, %14, %15, %16, %17, %18, %19, %20, %21, %22, %23, %24, %25, %26, %27, %28, %29, %30, %31, %32, %33, %34, %35, %36, %37, %38, %39, %40, %41, %42, %43, %44, %45, %46, %47, %48, %49, %50, %51, %52, %53, %54, %55, %56, %57, %58, %59, %60, %61, %62, %63}, {%64, %65, %66, %67}, %68, 1, 1, 1, 0;"
    : "+f"(d[0]), "+f"(d[1]), "+f"(d[2]), "+f"(d[3]), "+f"(d[4]), "+f"(d[5]), "+f"(d[6]), "+f"(d[7]), "+f"(d[8]), "+f"(d[9]), "+f"(d[10]), "+f"(d[11]), "+f"(d[12]), "+f"(d[13]), "+f"(d[14]), "+f"(d[15]), "+f"(d[16]), "+f"(d[17]), "+f"(d[18]), "+f"(d[19]), "+f"(d[20]), "+f"(d[21]), "+f"(d[22]), "+f"(d[23]), "+f"(d[24]), "+f"(d[25]), "+f"(d[26]), "+f"(d[27]), "+f"(d[28]), "+f"(d[29]), "+f"(d[30]), "+f"(d[31]), "+f"(d[32]), "+f"(d[33]), "+f"(d[34]), "+f"(d[35]), "+f"(d[36]), "+f"(d[37]), "+f"(d[38]), "+f"(d[39]), "+f"(d[40]), "+f"(d[41]), "+f"(d[42]), "+f"(d[43]), "+f"(d[44]), "+f"(d[45]), "+f"(d[46]), "+f"(d[47]), "+f"(d[48]), "+f"(d[49]), "+f"(d[50]), "+f"(d[51]), "+f"(d[52]), "+f"(d[53]), "+f"(d[54]), "+f"(d[55]), "+f"(d[56]), "+f"(d[57]), "+f"(d[58]), "+f"(d[59]), "+f"(d[60]), "+f"(d[61]), "+f"(d[62]), "+f"(d[63]) : "r"(a[0]), "r"(a[1]), "r"(a[2]), "r"(a[3]), "l"(db));
}
template <> DEV void wgmma_rs<112>(float* d, const u32* a, u64 db) {
  asm volatile("wgmma.mma_async.sync.aligned.m64n112k16.f32.bf16.bf16 {%0, %1, %2, %3, %4, %5, %6, %7, %8, %9, %10, %11, %12, %13, %14, %15, %16, %17, %18, %19, %20, %21, %22, %23, %24, %25, %26, %27, %28, %29, %30, %31, %32, %33, %34, %35, %36, %37, %38, %39, %40, %41, %42, %43, %44, %45, %46, %47, %48, %49, %50, %51, %52, %53, %54, %55}, {%56, %57, %58, %59}, %60, 1, 1, 1, 0;"
    : "+f"(d[0]), "+f"(d[1]), "+f"(d[2]), "+f"(d[3]), "+f"(d[4]), "+f"(d[5]), "+f"(d[6]), "+f"(d[7]), "+f"(d[8]), "+f"(d[9]), "+f"(d[10]), "+f"(d[11]), "+f"(d[12]), "+f"(d[13]), "+f"(d[14]), "+f"(d[15]), "+f"(d[16]), "+f"(d[17]), "+f"(d[18]), "+f"(d[19]), "+f"(d[20]), "+f"(d[21]), "+f"(d[22]), "+f"(d[23]), "+f"(d[24]), "+f"(d[25]), "+f"(d[26]), "+f"(d[27]), "+f"(d[28]), "+f"(d[29]), "+f"(d[30]), "+f"(d[31]), "+f"(d[32]), "+f"(d[33]), "+f"(d[34]), "+f"(d[35]), "+f"(d[36]), "+f"(d[37]), "+f"(d[38]), "+f"(d[39]), "+f"(d[40]), "+f"(d[41]), "+f"(d[42]), "+f"(d[43]), "+f"(d[44]), "+f"(d[45]), "+f"(d[46]), "+f"(d[47]), "+f"(d[48]), "+f"(d[49]), "+f"(d[50]), "+f"(d[51]), "+f"(d[52]), "+f"(d[53]), "+f"(d[54]), "+f"(d[55]) : "r"(a[0]), "r"(a[1]), "r"(a[2]), "r"(a[3]), "l"(db));
}
template <> DEV void wgmma_rs<96>(float* d, const u32* a, u64 db) {
  asm volatile("wgmma.mma_async.sync.aligned.m64n96k16.f32.bf16.bf16 {%0, %1, %2, %3, %4, %5, %6, %7, %8, %9, %10, %11, %12, %13, %14, %15, %16, %17, %18, %19, %20, %21, %22, %23, %24, %25, %26, %27, %28, %29, %30, %31, %32, %33, %34, %35, %36, %37, %38, %39, %40, %41, %42, %43, %44, %45, %46, %47}, {%48, %49, %50, %51}, %52, 1, 1, 1, 0;"
    : "+f"(d[0]), "+f"(d[1]), "+f"(d[2]), "+f"(d[3]), "+f"(d[4]), "+f"(d[5]), "+f"(d[6]), "+f"(d[7]), "+f"(d[8]), "+f"(d[9]), "+f"(d[10]), "+f"(d[11]), "+f"(d[12]), "+f"(d[13]), "+f"(d[14]), "+f"(d[15]), "+f"(d[16]), "+f"(d[17]), "+f"(d[18]), "+f"(d[19]), "+f"(d[20]), "+f"(d[21]), "+f"(d[22]), "+f"(d[23]), "+f"(d[24]), "+f"(d[25]), "+f"(d[26]), "+f"(d[27]), "+f"(d[28]), "+f"(d[29]), "+f"(d[30]), "+f"(d[31]), "+f"(d[32]), "+f"(d[33]), "+f"(d[34]), "+f"(d[35]), "+f"(d[36]), "+f"(d[37]), "+f"(d[38]), "+f"(d[39]), "+f"(d[40]), "+f"(d[41]), "+f"(d[42]), "+f"(d[43]), "+f"(d[44]), "+f"(d[45]), "+f"(d[46]), "+f"(d[47]) : "r"(a[0]), "r"(a[1]), "r"(a[2]), "r"(a[3]), "l"(db));
}
template <> DEV void wgmma_rs<80>(float* d, const u32* a, u64 db) {
  asm volatile("wgmma.mma_async.sync.aligned.m64n80k16.f32.bf16.bf16 {%0, %1, %2, %3, %4, %5, %6, %7, %8, %9, %10, %11, %12, %13, %14, %15, %16, %17, %18, %19, %20, %21, %22, %23, %24, %25, %26, %27, %28, %29, %30, %31, %32, %33, %34, %35, %36, %37, %38, %39}, {%40, %41, %42, %43}, %44, 1, 1, 1, 0;"
    : "+f"(d[0]), "+f"(d[1]), "+f"(d[2]), "+f"(d[3]), "+f"(d[4]), "+f"(d[5]), "+f"(d[6]), "+f"(d[7]), "+f"(d[8]), "+f"(d[9]), "+f"(d[10]), "+f"(d[11]), "+f"(d[12]), "+f"(d[13]), "+f"(d[14]), "+f"(d[15]), "+f"(d[16]), "+f"(d[17]), "+f"(d[18]), "+f"(d[19]), "+f"(d[20]), "+f"(d[21]), "+f"(d[22]), "+f"(d[23]), "+f"(d[24]), "+f"(d[25]), "+f"(d[26]), "+f"(d[27]), "+f"(d[28]), "+f"(d[29]), "+f"(d[30]), "+f"(d[31]), "+f"(d[32]), "+f"(d[33]), "+f"(d[34]), "+f"(d[35]), "+f"(d[36]), "+f"(d[37]), "+f"(d[38]), "+f"(d[39]) : "r"(a[0]), "r"(a[1]), "r"(a[2]), "r"(a[3]), "l"(db));
}
template <> DEV void wgmma_rs<64>(float* d, const u32* a, u64 db) {
  asm volatile("wgmma.mma_async.sync.aligned.m64n64k16.f32.bf16.bf16 {%0, %1, %2, %3, %4, %5, %6, %7, %8, %9, %10, %11, %12, %13, %14, %15, %16, %17, %18, %19, %20, %21, %22, %23, %24, %25, %26, %27, %28, %29, %30, %31}, {%32, %33, %34, %35}, %36, 1, 1, 1, 0;"
    : "+f"(d[0]), "+f"(d[1]), "+f"(d[2]), "+f"(d[3]), "+f"(d[4]), "+f"(d[5]), "+f"(d[6]), "+f"(d[7]), "+f"(d[8]), "+f"(d[9]), "+f"(d[10]), "+f"(d[11]), "+f"(d[12]), "+f"(d[13]), "+f"(d[14]), "+f"(d[15]), "+f"(d[16]), "+f"(d[17]), "+f"(d[18]), "+f"(d[19]), "+f"(d[20]), "+f"(d[21]), "+f"(d[22]), "+f"(d[23]), "+f"(d[24]), "+f"(d[25]), "+f"(d[26]), "+f"(d[27]), "+f"(d[28]), "+f"(d[29]), "+f"(d[30]), "+f"(d[31]) : "r"(a[0]), "r"(a[1]), "r"(a[2]), "r"(a[3]), "l"(db));
}
template <> DEV void wgmma_rs<48>(float* d, const u32* a, u64 db) {
  asm volatile("wgmma.mma_async.sync.aligned.m64n48k16.f32.bf16.bf16 {%0, %1, %2, %3, %4, %5, %6, %7, %8, %9, %10, %11, %12, %13, %14, %15, %16, %17, %18, %19, %20, %21, %22, %23}, {%24, %25, %26, %27}, %28, 1, 1, 1, 0;"
    : "+f"(d[0]), "+f"(d[1]), "+f"(d[2]), "+f"(d[3]), "+f"(d[4]), "+f"(d[5]), "+f"(d[6]), "+f"(d[7]), "+f"(d[8]), "+f"(d[9]), "+f"(d[10]), "+f"(d[11]), "+f"(d[12]), "+f"(d[13]), "+f"(d[14]), "+f"(d[15]), "+f"(d[16]), "+f"(d[17]), "+f"(d[18]), "+f"(d[19]), "+f"(d[20]), "+f"(d[21]), "+f"(d[22]), "+f"(d[23]) : "r"(a[0]), "r"(a[1]), "r"(a[2]), "r"(a[3]), "l"(db));
}
template <> DEV void wgmma_rs<32>(float* d, const u32* a, u64 db) {
  asm volatile("wgmma.mma_async.sync.aligned.m64n32k16.f32.bf16.bf16 {%0, %1, %2, %3, %4, %5, %6, %7, %8, %9, %10, %11, %12, %13, %14, %15}, {%16, %17, %18, %19}, %20, 1, 1, 1, 0;"
    : "+f"(d[0]), "+f"(d[1]), "+f"(d[2]), "+f"(d[3]), "+f"(d[4]), "+f"(d[5]), "+f"(d[6]), "+f"(d[7]), "+f"(d[8]), "+f"(d[9]), "+f"(d[10]), "+f"(d[11]), "+f"(d[12]), "+f"(d[13]), "+f"(d[14]), "+f"(d[15]) : "r"(a[0]), "r"(a[1]), "r"(a[2]), "r"(a[3]), "l"(db));
}
template <> DEV void wgmma_rs<16>(float* d, const u32* a, u64 db) {
  asm volatile("wgmma.mma_async.sync.aligned.m64n16k16.f32.bf16.bf16 {%0, %1, %2, %3, %4, %5, %6, %7}, {%8, %9, %10, %11}, %12, 1, 1, 1, 0;"
    : "+f"(d[0]), "+f"(d[1]), "+f"(d[2]), "+f"(d[3]), "+f"(d[4]), "+f"(d[5]), "+f"(d[6]), "+f"(d[7]) : "r"(a[0]), "r"(a[1]), "r"(a[2]), "r"(a[3]), "l"(db));
}

#define T_G 400
#define T_0 600
#define T_G2 300
#define NCR 1
#define A1 9
#define A2 13
#define T_U0 3900
#define T_UP 1700
#define N_T 2
#define D_U 1000
#define D_UH 1700
#define D_Y 2300
#define D_M 1900
#define D_H 1700
#define G_H 400
#define D_X 1200
#define T_W 11000
#define G_W 500
#define R0 3
#define PROF0 0
#define RDV 0
#define PROMO 2
#define T_X 0
#define T_PF 400
#define T_ZS 400
#define T_P 4200
#define KZ 1
#define TOK_S 11
#define G2ROT 0

template <int NW> DEV void phase_a(const Params& p, int j, int q, int role, int lane, u32 par) {
  const int o = lane & 3, cl = (8 * q + (lane >> 2)) * 2 * NW, c = 128 * j + 64 * (role & 1) + cl;
  const u32 ka = sb + j * KVP + o * 1024 + cl * 2;
  u32 sw[NW][4], k[11][NW], r[8][NW];
#pragma unroll
  for (int e = 0; e < NW; e++) lds128(sw[e], sb + SHK + c * 8 + e * 16);
#pragma unroll
  for (int i = 0; i < 11; i++) { if (NW == 2) lds64(k[i], ka + i * 128); else k[i][0] = lds32(ka + i * 128); }
#pragma unroll
  for (int i = 0; i < 8; i++) { if (NW == 2) lds64(r[i], ka + VO + i * 128); else r[i][0] = lds32(ka + VO + i * 128); }
  u16* dst = p.s->u + c * 2048 + 2040 - 32 * (role >> 1) - 8 * o;
#pragma unroll
  for (int e = 0; e < NW; e++) {
    const u32 w0 = prmt(sw[e][0], sw[e][2], 0x5410), w1 = prmt(sw[e][0], sw[e][2], 0x7632), w2 = prmt(sw[e][1], sw[e][3], 0x5410), w3 = prmt(sw[e][1], sw[e][3], 0x7632);
#pragma unroll
    for (int i = 0; i < 8; i++) r[i][e] = hmul2(hfma2(k[i + 3][e], w0, hfma2(k[i + 2][e], w1, hfma2(k[i + 1][e], w2, hmul2(k[i][e], w3)))), r[i][e]);
    r[7][e] = tagw(r[7][e], (o & 1) * 0x10001u, par);
    stg128(dst + e * 4096, make_uint4(prmt(r[7][e], r[6][e], 0x5410), prmt(r[5][e], r[4][e], 0x5410), prmt(r[3][e], r[2][e], 0x5410), prmt(r[1][e], r[0][e], 0x5410)));
    stg128(dst + e * 4096 + 2048, make_uint4(prmt(r[7][e], r[6][e], 0x7632), prmt(r[5][e], r[4][e], 0x7632), prmt(r[3][e], r[2][e], 0x7632), prmt(r[1][e], r[0][e], 0x7632)));
  }
}
template <int N, int STRIDE> DEV void shift_copy(u32 a, u32 dv, bool first) {
  uint4 w[N]; u32 pv[N];
#pragma unroll
  for (int i = 0; i < N; i++) { w[i] = lds128(a + i * STRIDE); pv[i] = lds32(a + i * STRIDE - 4); }
  if (first) { w[0].x = hadd2(w[0].x, dv); sts32(a, w[0].x); }
#pragma unroll
  for (int i = 0; i < N; i++)
    sts128(a + KO + i * STRIDE, make_uint4(prmt(pv[i], w[i].x, 0x5432), prmt(w[i].x, w[i].y, 0x5432), prmt(w[i].y, w[i].z, 0x5432), prmt(w[i].z, w[i].w, 0x5432)));
}
template <int S0, int S1> DEV void load_a(u32* a, u32 p) {
#pragma unroll
  for (int s = S0; s < S1; s++) { a[4 * s] = lds32(p + 256 * s); a[4 * s + 1] = lds32(p + 256 * s + 128); a[4 * s + 2] = lds32(p + 256 * s + 16); a[4 * s + 3] = lds32(p + 256 * s + 144); }
}
template <int S> DEV void load_a_if(u32* a, u32 p, bool c) {
  asm volatile("{\n.reg .pred q;\nsetp.ne.u32 q, %5, 0;\n@q ld.shared.b32 %0, [%4+%6];\n@q ld.shared.b32 %1, [%4+%7];\n@q ld.shared.b32 %2, [%4+%8];\n@q ld.shared.b32 %3, [%4+%9];\n}\n"
               : "+r"(a[4 * S]), "+r"(a[4 * S + 1]), "+r"(a[4 * S + 2]), "+r"(a[4 * S + 3])
               : "r"(p), "r"((u32)c), "n"(256 * S), "n"(256 * S + 128), "n"(256 * S + 16), "n"(256 * S + 144) : "memory");
}
template <int K> DEV void conv_pair(float* d, const u32* a, u32 lo) {
  wgmma_rs<256 - 32 * K>(d, a + 8 * K, desc_join(lo + 32 * K, 8u));
  wgmma_rs<240 - 32 * K>(d, a + 8 * K + 4, desc_join(lo + 32 * K + 16, 8u));
  wg_commit();
}
template <int K> DEV void conv_work(const float* d, u32* a, u32 ps, u32 pn, bool more) {
  constexpr int I = 7 - K;
  u32 pk[4];
  if constexpr (K >= R0) load_a_if<2 * (K - R0)>(a, pn, more);
#pragma unroll
  for (int e = 0; e < 4; e++) {
    const int nb = 4 * I + e;
    pk[e] = nb < 31 ? pack2(d[4 * nb] + d[(4 * nb + 6) & 127], d[4 * nb + 1] + d[(4 * nb + 7) & 127]) : pack2(d[4 * nb], d[4 * nb + 1]);
  }
  stsm4t(ps - 512 * I, pk);
  if constexpr (K >= R0) load_a_if<2 * (K - R0) + 1>(a, pn, more);
}
DEV int validate(u32 dst, const void* src, u32 bytes, bool fetched, u32 rbar, u32& rph, u32 off, u32 old) {
  int n = 0;
#pragma unroll 1
  while (true) {
    if (!fetched) { e_xload(dst, src, bytes, rbar); mbar_wait(rbar, rph); rph ^= 1; }
    fetched = false;
    u32 m = 1;
    const u32 a0 = dst + off, lim = a0 + bytes - 1024;
#pragma unroll 1
    for (u32 o = 0; o < bytes; o += 4096) {
      const u32 v0 = lds32(a0 + o), v1 = lds32(a0 + o + 1024), v2 = lds32(a0 + o + 2048), v3 = lds32(min(a0 + o + 3072, lim));
      m &= ((v0 ^ old) & (v1 ^ old)) & ((v2 ^ old) & (v3 ^ old));
    }
    if (__all_sync(0xffffffffu, m != 0)) break;
    trap_if_gt(++n, 1 << 16);
  }
  return n;
}
DEV void ln_post(float (*c)[4], u32 a, int lane) {
  const bool o = lane & 4;
  if ((lane & 3) == (lane >> 3)) sts128(a, make_uint4(__float_as_uint(c[0][0]), __float_as_uint(o ? c[1][1] : c[1][0]), __float_as_uint(c[0][2]), __float_as_uint(o ? c[2][3] : c[2][2])));
}
DEV void ln_params(u32 a, u32* r2, u32* n2) {
  u32 v[8][4];
#pragma unroll
  for (int i = 0; i < 8; i++) lds128(v[i], a + i * 128);
#pragma unroll
  for (int hh = 0; hh < 2; hh++) {
    auto sum = [&](int e) { return ((__uint_as_float(v[0][e]) + __uint_as_float(v[1][e])) + (__uint_as_float(v[2][e]) + __uint_as_float(v[3][e]))) +
                                   ((__uint_as_float(v[4][e]) + __uint_as_float(v[5][e])) + (__uint_as_float(v[6][e]) + __uint_as_float(v[7][e]))); };
    const float mu = sum(2 * hh) * (1.f / 640.f), rs = rsqrtf(fmaxf(sum(2 * hh + 1) * (1.f / 640.f) - mu * mu, 0.f) + 1e-5f);
    r2[hh] = pack2(rs, rs); n2[hh] = pack2(-mu * rs, -mu * rs);
  }
}
DEV void fetch_y(const Maps& tm, int j0, int j1, int role) {
  e_expect(bar(B_XF + 5 + (j0 >> 1)), 4096 * (j1 - j0));
#pragma unroll 1
  for (int j = j0; j < j1; j++) e_tma2d(sb + YS + j * 4096, &tm.y, bar(B_XF + 5 + (j0 >> 1)), 16 * (role & 3), (role >> 2) * 640 + 128 * j);
}
DEV float gelu2(float a) { return fmaf(a, tanh_fast(a * fmaf(0.035677408136300125f, a * a, 0.7978845608028654f)), a); }

template <int N>
DEV void gemm_pass(float* acc, u32* zp, int pass, u32& s, u32& ph, bool elect, u32 zsp, u32* z2p, int lane) {
  constexpr int NG = N / 8, PART = (NG + 3) / 4;
  const bool g2 = pass == 2;
  u32 la = g2 ? desc_lo(sb + AR, 16) : desc_lo(sb + XR, 1024);
  const u32 ha = g2 ? 0x40000040u : 8u, sa = g2 ? 2 : 128;
  const u32 lb0 = g2 ? desc_lo(sb + (N == 128 ? 0 : 2048), 3456) : N == 128 ? desc_lo(sb, 8192) : desc_lo(sb + 16384, 1408);
  const u32 hb = (N == 128 && !g2) ? 0x40000040u : 8u, st = g2 ? 432 : N == 128 ? 128 : 176;
  const int nk = g2 ? 32 : 10, ns = g2 ? 6 : 5, kz = pass == 1 ? KZ : 99;
  u32 bprev = 0;
#pragma unroll 1
  for (int k = 0; k < nk; k++) {
    const u32 bfull = sb + M_BAR + 8 * B_FULL + 8 * s, lb = lb0 + s * (BT >> 4);
    if (pass == 0) mbar_wait(bar(B_VAL) + 8 * (k >> 1), 0);
    mbar_wait(bfull, (ph >> s) & 1);
    PROF(k == 0 && elect && N == 128, 40 + pass);
    wg_fence();
#pragma unroll
    for (int q = 0; q < 4; q++) {
      if constexpr (N == 128) wgmma_ss_128(acc, desc_join(la + q * sa, ha), desc_join(lb + q * st, hb), (k | q) != 0);
      else wgmma_ss_88(acc, desc_join(la + q * sa, ha), desc_join(lb + q * st, hb), (k | q) != 0);
    }
    wg_commit();
    ph ^= 1u << s;
    la += (g2 && s == 4) ? -5 * 512 : 512;
    s = s + 1 == ns ? 0 : s + 1;
    wg_wait<1>();
    mbar_arrive_if(bprev, elect && k > 0);
    bprev = bfull + 8 * (B_EMPTY - B_FULL);
    if (k == kz) {
      mbar_wait(sb + M_BAR + 8 * B_ZS, 0);
      PROF(elect && N == 128, 47);
      const u32 v0 = lds32(zsp), v1 = lds32(zsp + 32);
      const u32 r0 = prmt(v0, v0, 0x1010), n0 = prmt(v0, v0, 0x3232), r1 = prmt(v1, v1, 0x1010), n1 = prmt(v1, v1, 0x3232);
#pragma unroll
      for (int n = 0; n < NG; n++) { zp[2 * n] = hfma2(zp[2 * n], r0, n0); zp[2 * n + 1] = hfma2(zp[2 * n + 1], r1, n1); }
    }
#pragma unroll
    for (int pt = 0; pt < 4; pt++)
      if (k == kz + pt) {
#pragma unroll
        for (int n = pt * PART; n < (pt + 1) * PART && n < NG; n++) {
          const int gp = N == 128 ? 4 + n : n < 4 ? n : 16 + n;
          stg32(z2p + gp * 32, zp[2 * n]); stg32(z2p + (27 + gp) * 32, zp[2 * n + 1]);
        }
        if (pt == 3) { __syncwarp(); mbar_arrive_if(sb + M_BAR + 8 * B_Z2D, lane == 0); }
      }
  }
  wg_wait<0>();
  mbar_arrive_if(bprev, elect);
}

DEV void spare_cta(const Params& p, const Maps& tm, int cq, int tid, int warp) {
  const int lane = tid & 31, kr = lane & 7, lg = lane >> 3, seg = warp % 3, kq = warp / 3;
  const u32 br = sb + M_BAR;
  e_init(br + 8 * warp, 1);
  const u32 ep = ld_rlx32(p.s->ctr);
  __syncthreads();
  auto issue = [&](int i) {
    const int pass = i >= 5, c0 = (pass ? 0 : 864) + 192 * cq, r0 = 128 * (i - 5 * pass);
    const u32 dst = sb + (i & 7) * 24576;
    e_expect(br + 8 * i, 24576);
    e_tma2d(dst, &tm.win32, br + 8 * i, c0 + (pass ? 128 : 0), r0);
    e_tma2d(dst + 8192, &tm.win32, br + 8 * i, c0 + 160, r0);
    e_tma2d(dst + 16384, &tm.win32, br + 8 * i, c0 + 768 - 168 * cq, r0);
  };
#define SPROF(i)
  if (warp == 0)
    for (int i = 0; i < 5; i++) issue(i);
#pragma unroll 1
  for (int i = 0; i < 10; i++) {
    if (warp == 1) {
      const int c0 = (i < 5 ? 896 : 0) + 192 * cq, r0 = 128 * (i < 5 ? i : i - 5);
      e_pf3d(&tm.win, c0, r0); e_pf3d(&tm.win, c0, r0 + 64);
    }
    mbar_wait(br + 8 * i, 0);
    SPROF(i);
    if (seg < 2 || lg < 3) {
      uint4 v[4];
#pragma unroll
      for (int e = 0; e < 4; e++) v[e] = lds128(sb + (i & 7) * 24576 + seg * 8192 + ((4 * e + kq) * 8 + kr) * 64 + ((lg ^ (kr >> 1)) << 4));
#pragma unroll
      for (int e = 0; e < 4; e++) stg128(p.s->ws + (((i >= 5 ? 240 : 0) + cq * 80 + 16 * i + 4 * e + kq) * 11 + seg * 4 + lg) * 64 + kr * 8, v[e]);
    }
    if (i == 4 || i == 9) {
      __syncthreads();
      if (tid == 0) { fence_gpu(); ctr_arrive(p.s->ctr, I_WS + (i >> 3), ep, tid); }
      SPROF(10 + (i >> 3));
      __syncthreads();
      if (warp == 0 && i == 4)
        for (int e = 5; e < 10; e++) issue(e);
    }
  }
#pragma unroll 1
  for (int b = 0; b < 2; b++) {
    if (warp == 0) e_expect(br + 80 + 8 * b, 432 * 320);
#pragma unroll 1
    for (int row = tid; row < 432; row += 384) {
      const int kg = 54 * b + (row >> 3), c2 = (cq + kg / 27) & 3, gm = kg % 27;
      load1d(sb + row * 336, p.wout + ((gm < 24 ? 24 * c2 + gm : 72 + 3 * c2 + gm) * 8 + (row & 7)) * 640 + 160 * cq, 320, br + 80 + 8 * b);
    }
    mbar_wait(br + 80 + 8 * b, 0);
    SPROF(12 + b);
#pragma unroll 1
    for (int u = warp * 4 + lg; u < 270; u += 48) {
      const u32 a = sb + ((u / 5) * 8 + kr) * 336 + (u % 5) * 64;
      const uint4 v0 = lds128(a), v1 = lds128(a + 16), v2 = lds128(a + 32), v3 = lds128(a + 48);
      u16* dst = p.s->wo + (cq * 540 + 270 * b + u) * 256 + kr * 8;
      stg128(dst, make_uint4(v0.x, v1.x, v2.x, v3.x));
      stg128(dst + 64, make_uint4(v0.y, v1.y, v2.y, v3.y));
      stg128(dst + 128, make_uint4(v0.z, v1.z, v2.z, v3.z));
      stg128(dst + 192, make_uint4(v0.w, v1.w, v2.w, v3.w));
    }
    __syncthreads();
  }
  if (tid == 0) { fence_gpu(); ctr_arrive(p.s->ctr, I_WO, ep, tid); }
  SPROF(14);
}

__global__ void __launch_bounds__(384, 1) mega_kernel(const __grid_constant__ Params p, const __grid_constant__ Maps tm) {
  extern __shared__ __align__(1024) unsigned char smem_raw[];
  const u32 t_start = clock();
  const int tid = threadIdx.x, warp = __shfl_sync(0xffffffffu, tid >> 5, 0), lane = tid & 31;
  int role;
  {
    u32 sm; asm volatile("mov.u32 %0, %%smid;" : "=r"(sm));
    const u32 x = sm - 64, q = (x * 4682u) >> 16;
    const u32 gpc = sm < 64 ? (sm & 15) >> 1 : 1 + ((x - 14 * q) >> 1) + (sm >= 120 ? 5 : 0);
    const u32 idx = (sm < 64 ? (sm >> 4) * 2 : 8 + 2 * q) + (sm & 1);
    role = sm >= 124 ? sm : (int)((0x5240643020100074ULL >> (8 * gpc)) & 0xff) + idx;
    role = __shfl_sync(0xffffffffu, role, 0);
  }
  if (role >= 128) { trap_if_gt(smem_u32(smem_raw) ^ sb, 0); spare_cta(p, tm, role - 128, tid, warp); return; }
  const int rt = role >> 2, cq = role & 3;

  e_init(bar(48 + warp), 2);
  if (warp == 8) {
    e_expect(bar(B_KV), KVP);
    e_tma2d(sb, &tm.k, bar(B_KV), 64 * (role & 1), 32 * (role >> 1) - 3);
    e_tma2d(sb + VO, &tm.v, bar(B_KV), 64 * (role & 1), 32 * (role >> 1));
    e_xload(sb + SHK, p.shk, 5120, bar(B_KV));
    PROF(lane == 0, 0);
  }
  if (warp < 6) e_tmpf(&tm.ssm + warp);
  e_init6(bar(warp), (u32)(0x111111a88881ull >> (4 * warp)) & 15);
  if (tid < 63) {
    sts128(sb + (tid < 5 ? US + tid * UP + 4096 : tid < 15 ? kslot((tid - 5) >> 1) - 16 + (tid & 1) * KO : PWB + ((tid - 15) & 7) * PWP + ((tid - 15) >> 3) * 16), make_uint4(0, 0, 0, 0));
    fence_async_smem();
  }
  __syncthreads();

  if (warp < 8) {
    asm volatile("setmaxnreg.inc.sync.aligned.u32 224;");
    u32 ep = ld_rlx32(p.s->ctr);
    const int wg = warp >> 2, w = warp & 3, t128 = tid & 127, g = lane >> 2, t = lane & 3;
    const bool elect = t128 == 0;
    const u32 ts = __shfl_sync(0xffffffffu, t_start, 0);
    PROF(tid == 0, 1);
    mbar_wait(bar(B_KV), 0);
    {
      const u32 koff = sb + ((g & 1) ? 0 : KO) + 4 * (t + (g >> 1) - 3) + 32 * w;
      const u32 pw = sb + PWB + wg * 4 * PWP;
      u32 a[64];
      const u32 dv = __ldg(p.ssmD + 128 * wg + role);
#pragma unroll 1
      for (int j = wg; j <= NCR * wg; j++) {
        mbar_wait(bar(B_KV + j), 0);
        stamp_post(p.s->ctr, S_U + j, ts, t128);
        PROF(elect, j < 2 ? 2 + j : 126);
        phase_a<1>(p, j, w, role, lane_now(), (ep & 1) - 1);
        PROF(elect, j < 2 ? 4 + j : 127);
        if (j < 2) {
          mbar_wait(bar(B_SS + wg), 0);
          shift_copy<2, 2048>(sb + kslot(wg) + t128 * 16, dv, elect);
          bsync(1 + wg, 128);
          load_a<0, 16>(a, koff + kslot(wg));
          PROFD(elect, 6 + wg, a[63]);
        }
      }
      ep = __shfl_sync(0xffffffffu, ep, 0);
#pragma unroll 1
      for (int ch = wg; ch < 5; ch += 2) {
        float d[128];
        const u32 pn = koff + kslot(ch + 2), ps = pw + w * (PWP + 32) + (255 - lane_now()) * 16, lo = desc_lo(sb + US + ch * UP, 16);
        const bool more = ch < 3;
        mbar_wait(bar(B_UV + ch), 0);
        if (ch > 0) bsync(3 + wg, 256);
        if (ch == 4) stamp_post(p.s->ctr, S_Y, ts, lane_now() + w);
        PROF(elect, 8 + ch);
        wg_fence();
        conv_pair<0>(d, a, lo); conv_pair<1>(d, a, lo); conv_pair<2>(d, a, lo);
        if (R0 == 0 && more) mbar_wait(bar(B_KB + ch), 0);
        wg_wait<2>();
        mbar_arrive_if(bar(B_EMPTY) + 8 * (ch == 1 ? w : ch - 1), w < (0x12020 >> (4 * ch) & 3) && lane_now() == 0);
        conv_work<0>(d, a, ps, pn, more); conv_pair<3>(d, a, lo);
        if (R0 == 1 && more) mbar_wait(bar(B_KB + ch), 0);
        wg_wait<2>(); conv_work<1>(d, a, ps, pn, more); conv_pair<4>(d, a, lo);
        if (R0 == 2 && more) mbar_wait(bar(B_KB + ch), 0);
        wg_wait<2>(); conv_work<2>(d, a, ps, pn, more); conv_pair<5>(d, a, lo); conv_pair<6>(d, a, lo); conv_pair<7>(d, a, lo);
        if (ch < 4) { if (RDV) bsync(4 - wg, 256); else barrive(4 - wg, 256); }
        if (R0 == 3 && more) mbar_wait(bar(B_KB + ch), 0);
        wg_wait<2>(); conv_work<3>(d, a, ps, pn, more); conv_work<4>(d, a, ps, pn, more); conv_work<5>(d, a, ps, pn, more);
        wg_wait<0>();
        PROFD(elect, 13 + ch, __float_as_uint(d[0]));
        conv_work<6>(d, a, ps, pn, more); conv_work<7>(d, a, ps, pn, more);
        bsync(1 + wg, 128);
        u32 q[2][4][4];
        const int t128 = 32 * w + lane_now();
#pragma unroll
        for (int h = 0; h < 2; h++)
#pragma unroll
          for (int i = 0; i < 4; i++) lds128(q[h][i], pw + i * PWP + h * 2048 + t128 * 16);
        if (more) load_a<16 - 2 * R0, 16>(a, pn);
        u16* yp = p.s->y + ((t128 >> 3) * 640 + 128 * ch + role) * 64 + ((t128 & 7) << 3);
#pragma unroll
        for (int h = 0; h < 2; h++) {
          u32 y[4];
#pragma unroll
          for (int e = 0; e < 4; e++) y[e] = hadd2(hadd2(q[h][0][e], q[h][1][e]), hadd2(q[h][2][e], q[h][3][e]));
          stg128(yp + h * (16 * 640 * 64), make_uint4(tagw(y[0], ~t128 & 1, ~ep), y[1], y[2], y[3]));
        }
        PROF(elect, 18 + ch);
      }
    }
    const u32 bs0 = hmul2((u32)__ldg(p.bsp + rt * 64 + 16 * w + g) * 0x10001u, 0x3f003f00u), bs1 = hmul2((u32)__ldg(p.bsp + rt * 64 + 16 * w + g + 8) * 0x10001u, 0x3f003f00u);
    {
      u32 x[5][4], x1[5][4], S[5][2], C[5][2], r2[2], n2[2];
      float c[3][4];
      const u32 xa = sb + QS + wg * 2048 + (lane & 15) * 128 + (((2 * w + (lane >> 4)) ^ (lane & 7)) << 4);
      const u32 ya = sb + YS + (16 * warp + (lane >> 4) * 8 + (lane & 7)) * 32 + ((((lane >> 3) ^ (lane >> 2)) & 1) << 4);
      const u32 ma = sb + M_MOD + 64 * (warp >> 1) + 16 * t + 8 * (warp & 1), la = sb + M_LN + g * 16, par = (ep & 1) - 1;
      auto clear = [&]() {
#pragma unroll
        for (int i = 0; i < 12; i++) c[i >> 2][i & 3] = 0.f;
      };
      mbar_wait(bar(B_Q), 0);
      PROF(elect, 23 + wg);
#pragma unroll
      for (int j = 0; j < 5; j++) ldsm4(x[j], xa + j * 4096);
      clear();
#pragma unroll
      for (int j = 0; j < 5; j++) row_stats(c, x[j]);
      ln_post(c, la + warp * 128, lane);
      bsync(5, 256);
      ln_params(la, r2, n2);
      PROFD(elect, 25 + wg, r2[0]);
#pragma unroll 1
      for (u32 ph = 0;; ph++) {
        u32 T[5][4], m = 1, bad = 0;
        mbar_wait(bar(B_XF + 7), ph & 1);
        PROF(elect && wg == 0 && ph == 0, 88);
#pragma unroll
        for (int j = 0; j < 5; j++) {
          u32 A[2], B[2], G[2];
          lds64(B, ma + j * 256); lds64(A, ma + j * 256 + 1280); lds64(G, ma + j * 256 + 2560); lds64(S[j], ma + j * 256 + 3840); lds64(C[j], ma + j * 256 + 5120);
#pragma unroll
          for (int i = 0; i < 2; i++) {
            m = min(min(min(m, A[i]), min(B[i], G[i])), min(S[j][i], C[j][i]));
            A[i] = hmul2(G[i], hadd2(A[i], ONE2)); B[i] = hmul2(G[i], B[i]); C[j][i] = hadd2(C[j][i], ONE2);
          }
#pragma unroll
          for (int i = 0; i < 4; i++) T[j][i] = hfma2(hfma2(x[j][i], r2[i & 1], n2[i & 1]), A[i >> 1], B[i >> 1]);
        }
        clear();
#pragma unroll
        for (int j = 0; j < 5; j++) {
          u32 y[4];
          if (j == 3) PROFD(elect && ph == 0, 27 + wg, __float_as_uint(c[2][0]));
          if (j == 0 || j == 3) mbar_wait(bar(B_XF + 5 + (j >> 1)), ph & 1);
          if (j == 3) tile_post(p.s->ctr + 32 + 32 * rt + cq, ts, ep, tid == 0);
          if (j == 0 || j == 3) PROF(elect && wg == 0 && ph == 0, 89 + j);
          ldsm4t(y, ya + j * 4096);
          bad |= (y[0] ^ par) | (y[2] ^ par);
#pragma unroll
          for (int i = 0; i < 4; i++) x1[j][i] = hfma2(y[i], T[j][i], x[j][i]);
          row_stats(c, x1[j]);
        }
        ln_post(c, la + 1024 + warp * 128, lane);
        PROFV(elect, 96, 100 * ph + 100);
        if (__all_sync(0xffffffffu, bsync_and(5, 256, m != 0 && (g != 0 || (bad & 0x10001) == 0)))) break;
        trap_if_gt(ph, 1 << 16);
        if (warp == 0) { fetch_y(tm, 0, 3, role); fetch_y(tm, 3, 5, role); e_xload(sb + M_MOD, p.s->mod, 6400, bar(B_XF + 7)); }
      }
      mbar_arrive_if(bar(B_HD), lane == 0);
      ln_params(la + 1024, r2, n2);
      PROFD(elect, 29 + wg, r2[0]);
      u32* hp = (u32*)p.s->h2 + ((rt * 80 + 2 * warp) * 8 + 2 * cq) * 32 + lane;
      const u32 m0 = (lane & 7) == 2 * cq, m1 = (lane & 7) == 2 * cq + 1;
#pragma unroll
      for (int j = 0; j < 5; j++)
#pragma unroll
        for (int i = 0; i < 4; i++)
          stg32(hp + (16 * j + (i >> 1)) * 256 + (i & 1) * 32, tagw(hfma2(hfma2(x1[j][i], r2[i & 1], n2[i & 1]), C[j][i >> 1], S[j][i >> 1]), (i & 1) ? m1 : m0, par));
      PROF(elect, 31 + wg);
      until(clock(), D_X);
      __syncwarp();
#pragma unroll
      for (int j = 0; j < 5; j++)
#pragma unroll
        for (int i = 0; i < 4; i++) stg32(hp + 32 * 80 * 8 * 32 + (16 * j + (i >> 1)) * 256 + (i & 1) * 32, x1[j][i]);
    }
    float z[64];
    u32 zp[32];
    u32* z2p = (u32*)p.s->z2 + (role * 8 + 2 * w) * 27 * 32 + lane;
    u32 s = 0, ph = 0;
#pragma unroll 1
    for (int pass = 0;; pass++) {
      if (wg == 0) gemm_pass<128>(z, zp, pass, s, ph, elect, sb + M_ZS + (16 * w + g) * 4, z2p, lane);
      else gemm_pass<88>(z, zp, pass, s, ph, elect, sb + M_ZS + (16 * w + g) * 4, z2p, lane);
      PROFD(tid == 0, 43 + pass, __float_as_uint(z[0]));
      if (pass == 2) break;
      float st[4] = {0.f, 0.f, 0.f, 0.f};
      auto act = [&](int n0, int n1) {
#pragma unroll
        for (int i = 2 * n0; i < 2 * n1; i++) {
          const float u0 = gelu2(z[2 * i]), u1 = gelu2(z[2 * i + 1]);
          zp[i] = pack2(u0, u1);
          st[2 * (i & 1)] += u0 + u1; st[2 * (i & 1) + 1] = fmaf(u1, u1, fmaf(u0, u0, st[2 * (i & 1) + 1]));
        }
      };
      if (wg == 0) act(11, 16);
      act(0, 11);
      if (pass == 0) {
        const bool up = t & 2;
        float a = (up ? st[2] : st[0]) + shx(up ? st[0] : st[2], 2), q = (up ? st[3] : st[1]) + shx(up ? st[1] : st[3], 2);
        a += shx(a, 1); q += shx(q, 1);
        if (!(t & 1))
          asm volatile("st.relaxed.gpu.global.v2.b32 [%0], {%1,%2};" ::"l"(p.s->stz + ((role * 2 + wg) * 64 + 16 * w + g + 4 * t)), "f"(a), "r"(prmt(__float_as_uint(q), ep + 1, 0x3214)) : "memory");
        __syncwarp();
        mbar_arrive_if(bar(B_ZP), lane == 0);
        PROF(tid == 0, 46);
      } else s = 5;
    }
    {
      u32* Pp = (u32*)p.s->P + ((role * 27 + 16 * wg) * 8 + 2 * w) * 32 + lane;
      const u32 Ps = sb + ((16 * wg + (lane >> 4)) * 8 + 2 * w) * 128 + (lane & 15) * 16;
      const u32 m0 = (lane & 7) == 2 * w, m1 = (lane & 7) == 2 * w + 1;
      auto gate = [&](int n0, int n1) {
#pragma unroll
        for (int n = n0; n < n1; n++) {
          zp[2 * n] = tagw(hmul2(zp[2 * n], hfma2(pack2(z[4 * n], z[4 * n + 1]), 0x3f003f00u, bs0)), m0, ~ep);
          zp[2 * n + 1] = tagw(hmul2(zp[2 * n + 1], hfma2(pack2(z[4 * n + 2], z[4 * n + 3]), 0x3f003f00u, bs1)), m1, ~ep);
          stg32(Pp + n * 256, zp[2 * n]); stg32(Pp + n * 256 + 32, zp[2 * n + 1]);
        }
      };
      gate(0, 11);
      if (wg == 0) gate(11, 16);
      bsync(5, 256);
      mbar_arrive_if(bar(B_PD), lane == 0);
#pragma unroll
      for (int n = 0; n < 10; n += 2) stsm4(Ps + n * 1024, zp + 2 * n);
      if (wg == 0) {
#pragma unroll
        for (int n = 10; n < 16; n += 2) stsm4(Ps + n * 1024, zp + 2 * n);
      } else stsm2(sb + XR + 2 * w * 128 + (lane & 15) * 16, zp[20], zp[21]);
      fence_async_smem();
    }
    if (wg == 0) barrive(5, 256);
    else {
      bsync(5, 256);
      PROF(elect, 48);
      float o[80];
      u32 gbv[20], x1f[40];
#pragma unroll
      for (int i = 0; i < 10; i++) ldg128(x1f + 4 * i, p.s->x1 + ((rt * 80 + 20 * cq + 4 * (i >> 1) + t) * 8 + 2 * w + (i & 1)) * 64 + g * 8);
#pragma unroll
      for (int i = 0; i < 5; i++) ldg128(gbv + 4 * i, p.s->mod + 3200 + 160 * cq + 32 * i + 8 * t);
      u32 la = desc_lo(sb, 1024), lb = desc_lo(sb + BT, 2560), bf = bar(B_WF), bprev = 0, s7 = 0, par = 0;
#pragma unroll 1
      for (int i = 0; i < 18; i++) {
        if (i == 4 || i == 9 || i == 13) { mbar_wait(bar(B_PV - 1) + 8 * (i >> 2), 0); PROF(elect, 48 + (i >> 2)); }
        mbar_wait(bf, par);
        wg_fence();
        wgmma_ss_160(o, desc_join(la, 8u), desc_join(lb, 8u), i != 0);
        la += i == 4 ? (XR >> 4) - 12 * 128 : 128;
        wgmma_ss_160(o, desc_join(la, 8u), desc_join(lb + 320, 8u), 1);
        wgmma_ss_160(o, desc_join(la + 128, 8u), desc_join(lb + 640, 8u), 1);
        wg_commit();
        la += 256;
        wg_wait<1>();
        mbar_arrive_if(bprev, elect && i > 0);
        bprev = bf + 8 * (B_WE - B_WF);
        const bool wrap = s7 == 6;
        s7 = wrap ? 0 : s7 + 1; par ^= wrap; bf += wrap ? -48 : 8; lb += wrap ? -6 * (int)(WOST >> 4) : (int)(WOST >> 4);
      }
      wg_wait<0>();
      PROFD(elect, 52, __float_as_uint(o[0]));
      u16* op = p.out + (rt * 64 + 16 * w + g) * 640 + 160 * cq + 8 * t;
#pragma unroll
      for (int i = 0; i < 10; i++) {
        const int be = i >> 1, h = i & 1;
        u32 r[4];
#pragma unroll
        for (int e = 0; e < 4; e++) r[e] = hfma2(pack2(o[16 * be + 4 * e + 2 * h], o[16 * be + 4 * e + 2 * h + 1]), gbv[4 * be + e], x1f[4 * i + e]);
        stg128(op + h * 8 * 640 + 32 * be, make_uint4(r[0], r[1], r[2], r[3]));
      }
      PROF(elect, 53);
    }
  } else {
    asm volatile("setmaxnreg.dec.sync.aligned.u32 56;");
    const int hw = warp - 8;
    if (hw == 0) {
      {
        const int n = lane, j = n < 15 ? (n * 11) >> 5 : n < 20 ? n - 15 : n - 20, ty = n < 15 ? n - 3 * j : n < 20 ? 3 : 4;
        const int c0 = ty < 2 ? 128 * j + 64 * (role & 1) : ty == 2 ? 0 : ty == 3 ? 32 * role : 64 * j;
        const int c1 = ty < 2 ? 32 * (role >> 1) - 3 + 3 * ty : ty == 2 ? 1024 * j + 8 * role : ty == 3 ? 128 * j : 16 * role;
        const u32 dst = sb + (ty < 2 ? j * KVP + ty * VO : ty == 2 ? kslot(j) : ty == 3 ? WM + j * 8192 : QS + j * 2048);
        const u32 br = bar(ty < 2 ? B_KV + j : ty == 2 ? B_SS + j : ty == 3 ? B_WM + j : B_Q), bytes = ty == 0 ? VO : ty < 3 ? 4096 : ty == 3 ? 8192 : 2048;
        int due = T_0 + 2 * T_G;
#pragma unroll 1
        for (int i = 2; i < 30; i++) {
          until(t_start, due);
          if (n == i) xtma2d(dst, &tm.k + ty, br, c0, c1, bytes);
          PROF(n == i, 96 + n);
          due += i < 15 ? T_G : i < 20 ? 2 * T_G2 : T_G2 / 2;
          __syncwarp();
        }
      }
      const u32 ep = ld_rlx32(p.s->ctr);
      u32 s = 0, ph = 32;
#pragma unroll 1
      for (int pass = 0; pass < 2; pass++) {
        ctr_poll(p.s->ctr, I_WS + pass, ep, 4);
        PROF(lane == 0, 33 + pass);
        const u16* src = p.s->ws + (pass * 4 + cq) * (80 * 11 * 64);
#pragma unroll 1
        for (int k = 0; k < 10; k++) {
          mbar_wait(bar(B_EMPTY + s), (ph >> s) & 1);
          until(t_start, T_W + k * G_W);
          PROF(lane == 0 && pass == 0 && k < 5, 74 + k);
          e_expect(bar(B_FULL + s), BT);
          e_tma3d(sb + s * BT, &tm.win, bar(B_FULL + s), (pass ? 0 : 896) + 192 * cq, 64 * k);
          e_load(sb + s * BT + 16384, src + k * 5632, 11264, bar(B_FULL + s));
          ph ^= 1u << s;
          s = s == 4 ? 0 : s + 1;
        }
      }
      mbar_wait(bar(B_Z2D), 0);
      PROF(lane == 0, 35);
      fence_gpu();
      ctr_arrive(p.s->ctr, I_Z2, ep, lane);
      PROF(lane == 0, 36);
      ctr_poll(p.s->ctr, I_Z2, ep, 128);
      PROF(lane == 0, 37);
      s = 5;
#pragma unroll 1
      for (int i = 0; i < 32; i++) {
        const int kt = (i + G2ROT * (rt & ~3)) & 31;
        mbar_wait(bar(B_EMPTY + s), (ph >> s) & 1);
        e_expect(bar(B_FULL + s), BT + 8192);
        e_load(sb + s * BT, p.s->z2 + (kt * 4 + cq) * (BT / 2), BT, bar(B_FULL + s));
        e_tma2d(sb + AR + (s == 5 ? 0 : s + 1) * 8192, &tm.wsp, bar(B_FULL + s), 64 * kt, 64 * rt);
        ph ^= 1u << s;
        s = s == 5 ? 0 : s + 1;
      }
      tile_post(p.s->ctr + 36 + 32 * rt + cq, t_start, ep, lane == 0);
      if (role == 0 && lane < 16 && lane != 1) p.s->ctr[lane] = lane ? 0 : ep + 1;
      ctr_poll(p.s->ctr, I_WO, ep, 4);
      PROF(lane == 0, 94);
      s = 0;
#pragma unroll 1
      for (int i = 0; i < 18; i++) {
        const int sl = 1 + ((i + 1) >> 1);
        mbar_wait(i < 7 ? bar(B_EMPTY + sl) : bar(B_WE + s), i < 7 ? (ph >> sl) & 1 : i >= 14);
        e_xload(sb + BT + s * WOST, p.s->wo + (cq * 18 + i) * (WOST / 2), WOST, bar(B_WF + s));
        s = s == 6 ? 0 : s + 1;
      }
    } else {
      u32 rph = 0, ep = ld_rlx32(p.s->ctr);
      if (hw == 1) {
        tile_wait(p.s->ctr + 36 + 32 * rt, ep - 1);
        uint2 sv = make_uint2(0, 0);
#pragma unroll 1
        for (int j = 0; j < 5; j++) {
          until(t_start, j < N_T ? T_U0 + j * T_UP : stamp_wait(p.s->ctr, S_U + j, sv) + (j > NCR ? D_UH : D_U));
          const u16* src = p.s->u + (128 * j + role) * 2048;
          e_xload(sb + US + j * UP, src, 4096, bar(B_XF + j));
          PROF(lane == 0, j ? 53 + j : 38);
          sv = ld_rlx64(p.s->ctr + 4 + 2 * j + (lane >> 5));
          mbar_wait(bar(B_XF + j), 0);
          const int n = validate(sb + US + j * UP, src, 4096, true, bar(B_RF), rph, lane * 32, ep);
          e_arrive(bar(B_UV + j));
          PROF(lane == 0, 64 + j); PROFV(lane == 0, 69 + j, 100 * n + 100);
        }
        mbar_wait(bar(B_EMPTY + 3), 0);
        fetch_y(tm, 0, 3, role);
        PROF(lane == 0, 58);
        until(t_start, stamp_wait(p.s->ctr, S_Y) + D_Y);
        fetch_y(tm, 3, 5, role);
        PROF(lane == 0, 59);
        {
          mbar_wait(bar(B_XF + 6), 0);
          const u32 t0 = t_start + tile_wait(p.s->ctr + 32 + 32 * rt, ep);
          mbar_wait(bar(B_HD), 0);
#pragma unroll 1
          for (int j = 0; j < 5; j++) {
            until(t0, D_H + j * G_H);
            e_xload(sb + XR + j * 16384, p.s->h2 + (rt * 5 + j) * 8192, 16384, bar(B_SS + j));
            PROF(lane == 0 && j == 0, 60);
          }
        }
        const u32 t0 = clock();
#pragma unroll 1
        for (int i = 0; i < 16; i++) { until(t0, i * T_PF); e_prefetch(p.wsp + (role * 16 + i) * 2048, 4096); }
      } else {
        const int hi = hw - 2;
        const u32 ts = __shfl_sync(0xffffffffu, t_start, 0);
        const u32 d0 = __ldg(p.ssmD + 128 * min(lane, 4) + role);
        {
          const int ht = tid - 320, g = lane >> 2, t = lane & 3;
          u32 cv[5];
#pragma unroll
          for (int i = 0; i < 5; i++) cv[i] = __ldg((const u32*)p.c + ht + 64 * i);
#pragma unroll 1
          for (int i = 0; i < 5; i++) {
            const float a = bflo(cv[0]), b = bfhi(cv[0]);
            const u32 v = pack2(__fdividef(a, 1.f + __expf(-a)), __fdividef(b, 1.f + __expf(-b))), ad = sb + M_SC + i * 256 + hi * 128 + t * 32 + g * 2;
            sts16(ad, v); sts16(ad + 16, v >> 16);
#pragma unroll
            for (int j = 0; j < 4; j++) cv[j] = cv[j + 1];
          }
          __syncwarp();
        }
        mbar_wait(bar(B_KV), 0);
        ep = __shfl_sync(0xffffffffu, ep, 0);
        const u64 dv = ((u64)(__shfl_sync(0xffffffffu, d0, 3) | __shfl_sync(0xffffffffu, d0, 4) << 16) << 32) | __shfl_sync(0xffffffffu, d0, 2) << 16;
#pragma unroll 1
        for (int j = 2; j < 5; j++) {
          const int lane = lane_now(), ht = 32 * hi + lane;
          if (j > NCR) {
            mbar_wait(bar(B_KV + j), 0);
            stamp_post(p.s->ctr, S_U + j, ts, ht);

            phase_a<2>(p, j, hi, role, lane, (ep & 1) - 1);
            PROF(ht == 0 && j == 4, 79);
          }
          mbar_wait(bar(B_SS + j), 0);
          shift_copy<4, 1024>(sb + kslot(j) + hi * 512 + lane_now() * 16, (u32)(dv >> (16 * j - 16)) & 0xffff, hi + lane_now() == 0);
          __syncwarp();
          e_arrive(bar(B_KB + j - 2));
          PROF(ht == 0, 78 + j);
        }
        const int lane = lane_now(), ht = 32 * hi + lane, g = lane >> 2;
        bsync(6, 64);
        mbar_arrive_if(bar(B_EMPTY) + 8 * hi, lane == 0);
        {
          float acc[8] = {0.f, 0.f, 0.f, 0.f, 0.f, 0.f, 0.f, 0.f};
#pragma unroll 1
          for (int j = 0; j < 5; j++) {
            u32 cv[4], wv[8][4];
            mbar_wait(bar(B_WM + j), 0);
            if (j == 4) stamp_post(p.s->ctr, S_MOD, ts, ht);
            PROF(ht == 0, 83 + j);
            lds128(cv, sb + M_SC + j * 256 + hi * 128 + g * 16);
#pragma unroll
            for (int i = 0; i < 8; i++) lds128(wv[i], sb + WM + j * 8192 + hi * 4096 + i * 512 + lane * 16);
#pragma unroll
            for (int i = 0; i < 8; i++) {
              const float c = (i & 1) ? bfhi(cv[i >> 1]) : bflo(cv[i >> 1]);
#pragma unroll
              for (int e = 0; e < 4; e++) { acc[2 * e] = fmaf(bflo(wv[i][e]), c, acc[2 * e]); acc[2 * e + 1] = fmaf(bfhi(wv[i][e]), c, acc[2 * e + 1]); }
            }
          }
          const u32 pa = sb + WM + hi * 4096;
          sts128(pa + lane * 32, make_uint4(__float_as_uint(acc[0]), __float_as_uint(acc[1]), __float_as_uint(acc[2]), __float_as_uint(acc[3])));
          sts128(pa + lane * 32 + 16, make_uint4(__float_as_uint(acc[4]), __float_as_uint(acc[5]), __float_as_uint(acc[6]), __float_as_uint(acc[7])));
          bsync(6, 64);
          float s0 = 0.f, s1 = 0.f;
          const int wd = lane & 15;
          const u32 ra = sb + WM + (role < 100 ? (wd & 3) * 32 + (wd >> 2) * 8 : wd * 8);
#pragma unroll
          for (int i = 0; i < 16; i++) { u32 v[2]; lds64(v, ra + (i >> 3) * 4096 + (i & 7) * 128); s0 += __uint_as_float(v[0]); s1 += __uint_as_float(v[1]); }
          if (ht < 16) stg32((u32*)p.s->mod + role * 16 + ht, nz(pack2(s0, s1)));
          consume(__float_as_uint(s0));
          bsync(6, 64);
          mbar_arrive_if(bar(B_EMPTY + 3), ht == 0);
          PROF(ht == 0, 39);
        }
        if (hi == 0) {
          until(ts, stamp_wait(p.s->ctr, S_MOD) + D_M);
          PROF(lane == 0, 95);
          e_xload(sb + M_MOD, p.s->mod, 6400, bar(B_XF + 7));
        }
#pragma unroll 1
        for (int i = 0; i < 5; i++) {
          mbar_wait(bar(B_SS + i), 1);
          PROF(ht == 0 && i == 0, 61);
          const int n = validate(sb + XR + i * 16384 + hi * 8192, p.s->h2 + (rt * 5 + i) * 8192 + hi * 4096, 8192, true, bar(B_RF + hw - 1), rph, lane * 32 + g * 4, ep);
          e_arrive(bar(B_VAL + i));
          if (i == 0) e_arrive(bar(B_EMPTY + 4));
          PROF(ht == 0 && (i == 0 || i == 4), i ? 63 : 62); PROFV(ht == 0 && n, 97, 100 * i + 100);
        }
        {
          mbar_wait(bar(B_ZP), 0);
          until(clock(), T_ZS);
          float s, q;
          int n = 0;
#pragma unroll 1
          while (true) {
            uint2 v[8];
            u32 bad = 0;
#pragma unroll
            for (int i = 0; i < 8; i++) v[i] = ld_rlx64(p.s->stz + (rt * 8 + i) * 64 + ht);
            s = 0.f; q = 0.f;
#pragma unroll
            for (int i = 0; i < 8; i++) { bad |= v[i].y ^ (ep + 1); s += __uint_as_float(v[i].x); q += __uint_as_float(v[i].y); }
            if (__all_sync(0xffffffffu, (bad & 255) == 0)) break;
            trap_if_gt(++n, 1 << 20);
          }
          const float mu = s * (1.f / 864.f), rs = rsqrtf(fmaxf(q * (1.f / 864.f) - mu * mu, 0.f) + 4e-5f);
          sts32(sb + M_ZS + ht * 4, pack2(rs, -mu * rs));
          __syncwarp();
          e_arrive(bar(B_ZS));
        }
        mbar_wait(bar(B_FULL + 5), 0);
        if (ht < 16 && role < 100) stg32((u32*)p.s->mod + role * 16 + ht, 0);
        __syncwarp();
      }
      mbar_wait(bar(B_WF), 0);
      const int tp = tile_wait(p.s->ctr + 36 + 32 * rt, ep);
      mbar_wait(bar(B_PD), 0);
      until(t_start, tp + T_P);
      validate(sb + XR + 1024 + (hw - 1) * BT, p.s->P + (rt * 4 + ((cq + hw) & 3)) * (BT / 2), BT, false, bar(B_RF + hw - 1), rph, lane_now() * 33 & ~3, ep);
      e_arrive(bar(B_PV + hw - 1));
    }
  }
}

typedef CUresult (*EncodeFn)(CUtensorMap*, CUtensorMapDataType, cuuint32_t, void*, const cuuint64_t*, const cuuint64_t*, const cuuint32_t*,
                             const cuuint32_t*, CUtensorMapInterleave, CUtensorMapSwizzle, CUtensorMapL2promotion, CUtensorMapFloatOOBfill);

extern "C" void kernel_launch(void* const* d_in, const int* in_sizes, int n_in, void* d_out, int out_size) {
  static EncodeFn enc = nullptr;
  if (!enc) {
    void* fn = nullptr; cudaDriverEntryPointQueryResult st;
    cudaGetDriverEntryPoint("cuTensorMapEncodeTiled", &fn, cudaEnableDefault, &st);
    enc = (EncodeFn)fn;
    cudaFuncSetAttribute(mega_kernel, cudaFuncAttributeMaxDynamicSharedMemorySize, SMEM_BYTES);
  }
  Params p;
  p.shk = (const u16*)d_in[3]; p.ssmD = (const u16*)d_in[5];
  p.wsp = (const u16*)d_in[8]; p.bsp = (const u16*)d_in[9]; p.wout = (const u16*)d_in[10]; p.c = (const u16*)d_in[11];
  p.out = (u16*)d_out;
  cudaGetSymbolAddress((void**)&p.s, g_s);
  auto mk = [&](void* base, int rank, cuuint64_t d0, cuuint64_t d1, cuuint32_t b0, cuuint32_t b1, CUtensorMapSwizzle sw) {
    CUtensorMap m;
    cuuint64_t gd[3] = {d0, d1, 2}, gs[2] = {d0 * 2, 128};
    cuuint32_t bd[3] = {b0, b1, 2}, es[3] = {1, 1, 1};
    enc(&m, CU_TENSOR_MAP_DATA_TYPE_BFLOAT16, rank, base, gd, gs, bd, es, CU_TENSOR_MAP_INTERLEAVE_NONE, sw, (CUtensorMapL2promotion)PROMO,
        CU_TENSOR_MAP_FLOAT_OOB_FILL_NONE);
    return m;
  };
  Maps tm;
  tm.k = mk(d_in[1], 2, 640, 2048, 64, 35, CU_TENSOR_MAP_SWIZZLE_NONE);
  tm.v = mk(d_in[2], 2, 640, 2048, 64, 32, CU_TENSOR_MAP_SWIZZLE_NONE);
  tm.ssm = mk(d_in[4], 2, 256, 5120, 256, 8, CU_TENSOR_MAP_SWIZZLE_NONE);
  tm.wmod = mk(d_in[12], 2, 3840, 640, 32, 128, CU_TENSOR_MAP_SWIZZLE_NONE);
  tm.q = mk(d_in[0], 2, 640, 2048, 64, 16, CU_TENSOR_MAP_SWIZZLE_128B);
  tm.win = mk(d_in[7], 3, 1728, 640, 64, 64, CU_TENSOR_MAP_SWIZZLE_128B);
  tm.wsp = mk(d_in[8], 2, 2048, 2048, 64, 64, CU_TENSOR_MAP_SWIZZLE_128B);
  tm.y = mk(p.s->y, 2, 64, 20480, 16, 128, CU_TENSOR_MAP_SWIZZLE_32B);
  tm.win32 = mk(d_in[7], 2, 1728, 640, 32, 128, CU_TENSOR_MAP_SWIZZLE_64B);
  mega_kernel<<<132, 384, SMEM_BYTES>>>(p, tm);
}
```

```cpp
#include <cuda_runtime.h>
#include <cuda.h>
#include <cuda_bf16.h>
#include <stdint.h>

typedef uint16_t u16; typedef uint32_t u32; typedef unsigned long long u64;
#define DEV __device__ __forceinline__

struct Scratch {
  u32 ctr[1280];
  u16 mod[4096];
  u64 stz[128 * 64 * 2];
  u16 u[640 * 2048];
  u16 y[32 * 640 * 64];
  u16 h2[32 * 80 * 8 * 64];
  u16 x1[32 * 80 * 8 * 64];
  u16 ws[2 * 4 * 80 * 11 * 64];
  u16 wo[4 * 108 * 20 * 64];
  u16 z2[32 * 4 * 8 * 27 * 64];
  u16 P[32 * 4 * 27 * 8 * 64];
};
__device__ __align__(1024) Scratch g_s;
enum { I_WS = 0, I_WO = 2, I_Z2 = 3 };
enum { S_Y = 0, S_MOD = 1, S_Z = 2, S_P = 3 };

struct Maps { CUtensorMap k, v, ssm, wmod, q, win, wsp, y, win32, wout; };
struct Params {
  Scratch* s;
  const u16 *shk, *ssmD, *c, *wsp, *bsp;
  u16* out;
};

constexpr u32 sb = 1024;
constexpr u32 BT = 27648, XR = 5 * BT, AR = 6 * BT, MISC = XR + 81920, SMEM_BYTES = 232448;
constexpr u32 M_LN = MISC, M_BAR = MISC + 2048, M_MOD = M_BAR + 1024, M_ZS = M_MOD + 7680, M_SM = M_ZS + 256, M_PROF = M_SM + 256;
constexpr u32 M_SC = M_MOD, M_TZ = M_SM, M_D = M_SM + 16;
constexpr u32 US = XR, UP = 4224, PWB = US + 5 * UP, PWP = 4192, YR = 2 * BT, KP = 8320, KO = 4144, WM = YR + 41984;
constexpr u32 KVP = 8576, VO = 4480, SHK = 5 * KVP, YS = XR - 20480, QS = XR + 55296, WOST = 15360;
DEV u32 kslot(int j) { return YR + 128 + j * KP; }
enum { B_WM = 0, B_RF = 5, B_SS = 8, B_PV = 13, B_YF = 19, B_RES = 22, B_FULL = 23, B_WO = 29, B_TOK = 30, B_WF = 33, B_WE = 40,
       B_VAL = 48, B_KB = 53, B_KV = 56, B_EMPTY = 61, B_WS1 = 67, B_ZS = 71,
       B_DUMMY = 72, B_HD = 73, B_ZP = 74, B_PD = 75, B_Z2D = 76, B_Q = 77, B_UV = 78,
       B_ZV = 84 };
DEV constexpr u32 bar(int i) { return sb + M_BAR + 8 * i; }

#define RST(i)
#define PROF(cond, i)
#define PROFD(cond, i, dep)
#define PROFV(cond, i, v)
#define PROFG(cond, i)

DEV u32 smem_u32(const void* p) { return (u32)__cvta_generic_to_shared(p); }
DEV void wg_fence() { asm volatile("wgmma.fence.sync.aligned;" ::: "memory"); }
DEV void wg_commit() { asm volatile("wgmma.commit_group.sync.aligned;" ::: "memory"); }
template <int N> DEV void wg_wait() { asm volatile("wgmma.wait_group.sync.aligned %0;" ::"n"(N) : "memory"); }
DEV u64 desc_join(u32 lo, u32 hi) { return ((u64)hi << 32) | lo; }
DEV constexpr u32 desc_lo(u32 addr, u32 lbo) { return ((addr & 0x3FFFF) >> 4) | ((lbo >> 4) << 16); }
DEV void mbar_init(u32 bar, int cnt) { asm volatile("mbarrier.init.shared::cta.b64 [%0], %1;" ::"r"(bar), "r"(cnt) : "memory"); }
DEV void mbar_arrive(u32 bar) { asm volatile("mbarrier.arrive.shared::cta.b64 _, [%0];" ::"r"(bar) : "memory"); }
DEV void mbar_arrive_if(u32 bar, bool c) { asm volatile("{\n.reg .pred p;\nsetp.ne.u32 p, %1, 0;\n@p mbarrier.arrive.shared::cta.b64 _, [%0];\n}\n" ::"r"(bar), "r"((u32)c) : "memory"); }
DEV void mbar_wait(u32 bar, u32 parity) {
  asm volatile("{\n.reg .pred p, q;\n.reg .u32 n;\nmov.u32 n, 0;\nW_LOOP:\nmbarrier.try_wait.parity.shared::cta.b64 p, [%0], %1;\n"
               "add.u32 n, n, 4;\nsetp.gt.u32 q, n, 4194304;\n@q st.shared.u32 [n], n;\n@!p bra W_LOOP;\n}\n" ::"r"(bar), "r"(parity) : "memory");
}
DEV bool mbar_test(u32 bar, u32 parity) {
  u32 ok;
  asm volatile("{\n.reg .pred p;\nmbarrier.test_wait.parity.shared::cta.b64 p, [%1], %2;\nselp.u32 %0, 1, 0, p;\n}\n" : "=r"(ok) : "r"(bar), "r"(parity) : "memory");
  return ok;
}
DEV void trap_if_gt(int n, int lim) { asm volatile("{\n.reg .pred p;\nsetp.gt.s32 p, %0, %1;\n@p st.shared.u32 [%2], %0;\n}\n" ::"r"(n), "r"(lim), "r"(0x400000) : "memory"); }
DEV void until(u32 t0, int c) { while ((int)(clock() - t0) < c) {} }
DEV void bsync(int id, int n) { asm volatile("bar.sync %0, %1;" ::"r"(id), "r"(n) : "memory"); }
DEV bool bsync_and(int id, int n, bool v) {
  u32 r;
  asm volatile("{\n.reg .pred p, q;\nsetp.ne.u32 p, %3, 0;\nbarrier.red.and.aligned.pred q, %1, %2, p;\nselp.u32 %0, 1, 0, q;\n}\n" : "=r"(r) : "r"(id), "r"(n), "r"((u32)v) : "memory");
  return r;
}
DEV void barrive(int id, int n) { asm volatile("bar.arrive %0, %1;" ::"r"(id), "r"(n) : "memory"); }
DEV void fence_async_smem() { asm volatile("fence.proxy.async.shared::cta;" ::: "memory"); }
DEV void fence_gpu() { asm volatile("fence.acq_rel.gpu;" ::: "memory"); }
#define ELECT "{\n.reg .pred p;\nelect.sync _|p, 0xffffffff;\n"
DEV void e_init(u32 bar, int cnt) { asm volatile(ELECT "@p mbarrier.init.shared::cta.b64 [%0], %1;\n}\n" ::"r"(bar), "r"(cnt) : "memory"); }
DEV void e_init6(u32 b, int cnt) {
  asm volatile(ELECT "@p mbarrier.init.shared::cta.b64 [%0], 1;\n@p mbarrier.init.shared::cta.b64 [%0+96], 1;\n@p mbarrier.init.shared::cta.b64 [%0+192], 1;\n"
               "@p mbarrier.init.shared::cta.b64 [%0+288], 1;\n@p mbarrier.init.shared::cta.b64 [%0+480], 2;\n@p mbarrier.init.shared::cta.b64 [%0+576], %1;\n@p mbarrier.init.shared::cta.b64 [%0+672], 3;\n}\n" ::"r"(b), "r"(cnt) : "memory");
}
DEV void e_expect(u32 bar, u32 bytes) { asm volatile(ELECT "@p mbarrier.arrive.expect_tx.shared::cta.b64 _, [%0], %1;\n}\n" ::"r"(bar), "r"(bytes) : "memory"); }
DEV void e_arrive(u32 bar) { asm volatile(ELECT "@p mbarrier.arrive.shared::cta.b64 _, [%0];\n}\n" ::"r"(bar) : "memory"); }
DEV void e_load(u32 dst, const void* src, u32 bytes, u32 bar) {
  asm volatile(ELECT "@p cp.async.bulk.shared::cluster.global.mbarrier::complete_tx::bytes [%0], [%1], %2, [%3];\n}\n" ::"r"(dst), "l"(src), "r"(bytes), "r"(bar) : "memory");
}
DEV void e_xload(u32 dst, const void* src, u32 bytes, u32 bar) {
  asm volatile(ELECT "@p mbarrier.arrive.expect_tx.shared::cta.b64 _, [%3], %2;\n@p cp.async.bulk.shared::cluster.global.mbarrier::complete_tx::bytes [%0], [%1], %2, [%3];\n}\n"
               ::"r"(dst), "l"(src), "r"(bytes), "r"(bar) : "memory");
}
DEV void e_tma2d(u32 dst, const void* tm, u32 bar, int c0, int c1) {
  asm volatile(ELECT "@p cp.async.bulk.tensor.2d.shared::cluster.global.mbarrier::complete_tx::bytes [%0], [%1, {%3, %4}], [%2];\n}\n" ::"r"(dst), "l"(tm), "r"(bar), "r"(c0), "r"(c1) : "memory");
}
DEV void e_tma3d(u32 dst, const void* tm, u32 bar, int c0, int c1) {
  asm volatile(ELECT "@p cp.async.bulk.tensor.3d.shared::cluster.global.mbarrier::complete_tx::bytes [%0], [%1, {%3, %4, %5}], [%2];\n}\n" ::"r"(dst), "l"(tm), "r"(bar), "r"(c0), "r"(c1), "r"(0) : "memory");
}
DEV void e_pf3d(const void* tm, int c0, int c1) {
  asm volatile(ELECT "@p cp.async.bulk.prefetch.tensor.3d.L2.global [%0, {%1, %2, %3}];\n}\n" ::"l"(tm), "r"(c0), "r"(c1), "r"(0) : "memory");
}
#define WAIT_EXPECT "{\n.reg .pred p, q;\n.reg .u32 n;\nmov.u32 n, 0;\nW_LOOP:\nmbarrier.try_wait.parity.shared::cta.b64 p, [%0], %1;\n" \
  "add.u32 n, n, 4;\nsetp.gt.u32 q, n, 4194304;\n@q st.shared.u32 [n], n;\n@!p bra W_LOOP;\nelect.sync _|p, 0xffffffff;\n@p mbarrier.arrive.expect_tx.shared::cta.b64 _, [%2], %3;\n"
template <int BYTES> DEV void w_load(u32 be, u32 par, u32 bf, u32 dst, const void* src) {
  asm volatile(WAIT_EXPECT "@p cp.async.bulk.shared::cluster.global.mbarrier::complete_tx::bytes [%4], [%5], %3, [%2];\n}\n"
               ::"r"(be), "r"(par), "r"(bf), "n"(BYTES), "r"(dst), "l"(src) : "memory");
}
DEV void w_g1(u32 be, u32 par, u32 bf, u32 dst, const void* tm, int c0, int c1, const void* src) {
  asm volatile(WAIT_EXPECT "@p cp.async.bulk.tensor.3d.shared::cluster.global.mbarrier::complete_tx::bytes [%4], [%5, {%6, %7, %8}], [%2];\n"
               "@p cp.async.bulk.shared::cluster.global.mbarrier::complete_tx::bytes [%9], [%10], 11264, [%2];\n}\n"
               ::"r"(be), "r"(par), "r"(bf), "n"(BT), "r"(dst), "l"(tm), "r"(c0), "r"(c1), "r"(0), "r"(dst + 16384), "l"(src) : "memory");
}
DEV void w_g2(u32 be, u32 par, u32 bf, u32 db, const void* src, u32 da, const void* tm, int c0, int c1) {
  asm volatile(WAIT_EXPECT "@p cp.async.bulk.shared::cluster.global.mbarrier::complete_tx::bytes [%4], [%5], %10, [%2];\n"
               "@p cp.async.bulk.tensor.2d.shared::cluster.global.mbarrier::complete_tx::bytes [%6], [%7, {%8, %9}], [%2];\n}\n"
               ::"r"(be), "r"(par), "r"(bf), "n"(BT + 8192), "r"(db), "l"(src), "r"(da), "l"(tm), "r"(c0), "r"(c1), "n"(BT) : "memory");
}
DEV void load1d(u32 dst, const void* src, u32 bytes, u32 bar) {
  asm volatile("cp.async.bulk.shared::cluster.global.mbarrier::complete_tx::bytes [%0], [%1], %2, [%3];" ::"r"(dst), "l"(src), "r"(bytes), "r"(bar) : "memory");
}
DEV void pf2d(const void* tm, int c0, int c1) { asm volatile("cp.async.bulk.prefetch.tensor.2d.L2.global [%0, {%1, %2}];" ::"l"(tm), "r"(c0), "r"(c1) : "memory"); }
DEV void xtma2d(u32 dst, const void* tm, u32 bar, int c0, int c1, u32 bytes) {
  asm volatile("mbarrier.arrive.expect_tx.shared::cta.b64 _, [%2], %5;\ncp.async.bulk.tensor.2d.shared::cluster.global.mbarrier::complete_tx::bytes [%0], [%1, {%3, %4}], [%2];"
               ::"r"(dst), "l"(tm), "r"(bar), "r"(c0), "r"(c1), "r"(bytes) : "memory");
}
DEV void xload(u32 dst, const void* src, u32 bytes, u32 bar) {
  asm volatile("mbarrier.arrive.expect_tx.shared::cta.b64 _, [%3], %2;\ncp.async.bulk.shared::cluster.global.mbarrier::complete_tx::bytes [%0], [%1], %2, [%3];"
               ::"r"(dst), "l"(src), "r"(bytes), "r"(bar) : "memory");
}
DEV void e_prefetch(const void* src, u32 bytes) { asm volatile(ELECT "@p cp.async.bulk.prefetch.L2.global [%0], %1;\n}\n" ::"l"(src), "r"(bytes) : "memory"); }
DEV void e_tmpf(const void* tm) { asm volatile(ELECT "@p prefetch.tensormap [%0];\n}\n" ::"l"(tm) : "memory"); }
DEV uint4 ld_nc(const void* p) { uint4 v; asm volatile("ld.global.nc.v4.u32 {%0,%1,%2,%3}, [%4];" : "=r"(v.x), "=r"(v.y), "=r"(v.z), "=r"(v.w) : "l"(p)); return v; }
DEV void ldg128(u32* v, const void* p) { asm volatile("ld.global.cg.v4.u32 {%0,%1,%2,%3}, [%4];" : "=r"(v[0]), "=r"(v[1]), "=r"(v[2]), "=r"(v[3]) : "l"(p) : "memory"); }
DEV uint4 ld_rlx128(const void* p) {
  u64 a, b; asm volatile("ld.relaxed.gpu.global.v2.b64 {%0,%1}, [%2];" : "=l"(a), "=l"(b) : "l"(p) : "memory");
  return make_uint4((u32)a, (u32)(a >> 32), (u32)b, (u32)(b >> 32));
}
DEV uint2 ld_rlx64(const void* p) { u64 a; asm volatile("ld.relaxed.gpu.global.b64 %0, [%1];" : "=l"(a) : "l"(p) : "memory"); return make_uint2((u32)a, (u32)(a >> 32)); }
DEV void cp16(u32 dst, const void* src) { asm volatile("cp.async.cg.shared.global [%0], [%1], 16;" ::"r"(dst), "l"(src) : "memory"); }
DEV void cp_wait() { asm volatile("cp.async.wait_all;" ::: "memory"); }
DEV void bulk_store(void* dst, u32 src, u32 bytes) {
  asm volatile("cp.async.bulk.global.shared::cta.bulk_group [%0], [%1], %2;\ncp.async.bulk.commit_group;" ::"l"(dst), "r"(src), "r"(bytes) : "memory");
}
DEV void bulk_wait() { asm volatile("cp.async.bulk.wait_group 0;" ::: "memory"); }
DEV u32 ld_rlx32(const void* p) { u32 a; asm volatile("ld.relaxed.gpu.global.u32 %0, [%1];" : "=r"(a) : "l"(p) : "memory"); return a; }
DEV void ctr_arrive(u32* ctr, int f, u32 ep, u32 sel) {
  asm volatile("{\n.reg .pred p;\nsetp.eq.u32 p, %2, 0;\n@p red.relaxed.gpu.global.add.u32 [%0], %1;\n}\n"
               ::"l"(ctr + 1 + sel), "r"((1u - 2u * (ep & 1)) << (8 * f)), "r"(sel) : "memory");
}
DEV void ctr_poll(u32* ctr, int f, u32 ep, u32 n) {
  const u32 want = (ep & 1) ? 0 : n;
  int it = 0;
#pragma unroll 1
  while (__any_sync(0xffffffffu, ((ld_rlx32(ctr + 1) >> (8 * f)) & 255) != want)) trap_if_gt(++it, 1 << 20);
}
DEV void stamp_post(u32* ctr, u32 ep, int i, u32 t0, u32 sel) {
  asm volatile("{\n.reg .pred p;\nsetp.eq.u32 p, %2, 0;\n@p red.relaxed.gpu.global.max.u32 [%0+4], %1;\n@p red.relaxed.gpu.global.add.u32 [%0], 1;\n}\n"
               ::"l"(ctr + 8 + 8 * (ep & 1) + 2 * i + sel), "r"((u32)clock() - t0), "r"(sel) : "memory");
}
DEV int stamp_wait(u32* ctr, u32 ep, int i) {
  uint2 v = make_uint2(0, 0);
  int it = 0;
#pragma unroll 1
  while (__any_sync(0xffffffffu, v.x != 128)) { v = ld_rlx64(ctr + 8 + 8 * (ep & 1) + 2 * i); trap_if_gt(++it, 1 << 20); }
  return v.y;
}
DEV void tile_post(u32* w, u32 t0, u32 ep, bool c) { if (c) asm volatile("st.relaxed.gpu.global.u32 [%0], %1;" ::"l"(w), "r"(min((u32)clock() - t0, 0xfffffu) ^ ((ep + 1) << 20)) : "memory"); }
DEV int tile_wait(const u32* w, u32 ep) {
  u32 m;
  int it = 0;
#pragma unroll 1
  do {
    const uint2 a = ld_rlx64(w), b = ld_rlx64(w + 2);
    const u32 e = (ep + 1) << 20;
    m = max(max(a.x ^ e, a.y ^ e), max(b.x ^ e, b.y ^ e));
    trap_if_gt(++it, 1 << 20);
  } while (__any_sync(0xffffffffu, m >> 20));
  return m;
}
DEV void stg128(void* p, uint4 v) { asm volatile("st.global.v4.b32 [%0], {%1,%2,%3,%4};" ::"l"(p), "r"(v.x), "r"(v.y), "r"(v.z), "r"(v.w) : "memory"); }
DEV void stg32(void* p, u32 v) { asm volatile("st.global.b32 [%0], %1;" ::"l"(p), "r"(v) : "memory"); }
DEV void stg32_if(void* p, u32 v, bool c) { asm volatile("{\n.reg .pred q;\nsetp.ne.u32 q, %2, 0;\n@q st.global.b32 [%0], %1;\n}\n" ::"l"(p), "r"(v), "r"((u32)c) : "memory"); }
DEV u32 lds32(u32 a) { u32 v; asm volatile("ld.shared.b32 %0, [%1];" : "=r"(v) : "r"(a) : "memory"); return v; }
DEV void lds64(u32* v, u32 a) { asm volatile("ld.shared.v2.b32 {%0,%1}, [%2];" : "=r"(v[0]), "=r"(v[1]) : "r"(a) : "memory"); }
DEV uint4 lds128(u32 a) { uint4 v; asm volatile("ld.shared.v4.b32 {%0,%1,%2,%3}, [%4];" : "=r"(v.x), "=r"(v.y), "=r"(v.z), "=r"(v.w) : "r"(a) : "memory"); return v; }
DEV void lds128(u32* v, u32 a) { asm volatile("ld.shared.v4.b32 {%0,%1,%2,%3}, [%4];" : "=r"(v[0]), "=r"(v[1]), "=r"(v[2]), "=r"(v[3]) : "r"(a) : "memory"); }
DEV void sts16(u32 a, u32 v) { asm volatile("st.shared.b16 [%0], %1;" ::"r"(a), "h"((u16)v) : "memory"); }
DEV void sts32(u32 a, u32 v) { asm volatile("st.shared.b32 [%0], %1;" ::"r"(a), "r"(v) : "memory"); }
DEV void sts64f(u32 a, float x, float y) { asm volatile("st.shared.v2.f32 [%0], {%1,%2};" ::"r"(a), "f"(x), "f"(y) : "memory"); }
DEV void sts128(u32 a, uint4 v) { asm volatile("st.shared.v4.b32 [%0], {%1,%2,%3,%4};" ::"r"(a), "r"(v.x), "r"(v.y), "r"(v.z), "r"(v.w) : "memory"); }
DEV void consume(u32 x) { asm volatile("{\n.reg .pred p;\nsetp.eq.u32 p, %0, 0x7fc12345;\n@p nanosleep.u32 0;\n}\n" ::"r"(x) : "memory"); }
DEV int lane_now() { int l; asm volatile("mov.u32 %0, %%laneid;" : "=r"(l)); return l; }
DEV u32 opaque(u32 x) { asm volatile("" : "+r"(x)); return x; }
DEV void ldsm4(u32* r, u32 a) { asm volatile("ldmatrix.sync.aligned.m8n8.x4.shared.b16 {%0,%1,%2,%3}, [%4];" : "=r"(r[0]), "=r"(r[1]), "=r"(r[2]), "=r"(r[3]) : "r"(a) : "memory"); }
DEV void ldsm4t(u32* r, u32 a) { asm volatile("ldmatrix.sync.aligned.m8n8.x4.trans.shared.b16 {%0,%1,%2,%3}, [%4];" : "=r"(r[0]), "=r"(r[1]), "=r"(r[2]), "=r"(r[3]) : "r"(a) : "memory"); }
DEV void stsm4(u32 a, const u32* r) { asm volatile("stmatrix.sync.aligned.m8n8.x4.shared.b16 [%0], {%1,%2,%3,%4};" ::"r"(a), "r"(r[0]), "r"(r[1]), "r"(r[2]), "r"(r[3]) : "memory"); }
DEV void stsm4t(u32 a, const u32* r) { asm volatile("stmatrix.sync.aligned.m8n8.x4.trans.shared.b16 [%0], {%1,%2,%3,%4};" ::"r"(a), "r"(r[0]), "r"(r[1]), "r"(r[2]), "r"(r[3]) : "memory"); }
DEV void stsm2(u32 a, u32 r0, u32 r1) { asm volatile("stmatrix.sync.aligned.m8n8.x2.shared.b16 [%0], {%1,%2};" ::"r"(a), "r"(r0), "r"(r1) : "memory"); }
DEV void mma16816(float* c, u32 a0, u32 a1, u32 a2, u32 a3, u32 b0, u32 b1) {
  asm volatile("mma.sync.aligned.m16n8k16.row.col.f32.bf16.bf16.f32 {%0,%1,%2,%3}, {%4,%5,%6,%7}, {%8,%9}, {%0,%1,%2,%3};"
      : "+f"(c[0]), "+f"(c[1]), "+f"(c[2]), "+f"(c[3]) : "r"(a0), "r"(a1), "r"(a2), "r"(a3), "r"(b0), "r"(b1));
}
constexpr u32 ONE2 = 0x3f803f80u;
DEV u32 prmt(u32 a, u32 b, u32 s) { u32 r; asm("prmt.b32 %0, %1, %2, %3;" : "=r"(r) : "r"(a), "r"(b), "r"(s)); return r; }
DEV u32 hmul2(u32 a, u32 b) { u32 r; asm("mul.rn.bf16x2 %0, %1, %2;" : "=r"(r) : "r"(a), "r"(b)); return r; }
DEV u32 hadd2(u32 a, u32 b) { u32 r; asm("add.rn.bf16x2 %0, %1, %2;" : "=r"(r) : "r"(a), "r"(b)); return r; }
DEV u32 hfma2(u32 a, u32 b, u32 c) { u32 r; asm("fma.rn.bf16x2 %0, %1, %2, %3;" : "=r"(r) : "r"(a), "r"(b), "r"(c)); return r; }
DEV void row_stats(float (*c)[4], const u32* x) {
  mma16816(c[0], x[0], x[1], x[2], x[3], ONE2, ONE2);
  mma16816(c[1], x[0], x[1], x[2], x[3], x[0], x[2]);
  mma16816(c[2], x[0], x[1], x[2], x[3], x[1], x[3]);
}
DEV u32 pack2(float lo, float hi) { u32 r; asm("cvt.rn.bf16x2.f32 %0, %1, %2;" : "=r"(r) : "f"(hi), "f"(lo)); return r; }
DEV float bflo(u32 w) { return __uint_as_float(w * 65536u); }
DEV float bfhi(u32 w) { return __uint_as_float(w & 0xffff0000u); }
DEV u32 tagw(u32 w, u32 m, u32 par) { return (w & ~m) | (par & m); }
DEV u32 nz(u32 w) { return max(w, 1u); }
DEV float tanh_fast(float x) { float r; asm("tanh.approx.f32 %0, %1;" : "=f"(r) : "f"(x)); return r; }
DEV float shx(float v, int m) { return __shfl_xor_sync(0xffffffffu, v, m); }
DEV void wgmma_ss_128(float* d, u64 da, u64 db, int sd) {
  asm volatile("{\n.reg .pred p;\nsetp.ne.b32 p, %66, 0;\nwgmma.mma_async.sync.aligned.m64n128k16.f32.bf16.bf16 {%0, %1, %2, %3, %4, %5, %6, %7, %8, %9, %10, %11, %12, %13, %14, %15, %16, %17, %18, %19, %20, %21, %22, %23, %24, %25, %26, %27, %28, %29, %30, %31, %32, %33, %34, %35, %36, %37, %38, %39, %40, %41, %42, %43, %44, %45, %46, %47, %48, %49, %50, %51, %52, %53, %54, %55, %56, %57, %58, %59, %60, %61, %62, %63}, %64, %65, p, 1, 1, 0, 1;\n}\n"
    : "+f"(d[0]), "+f"(d[1]), "+f"(d[2]), "+f"(d[3]), "+f"(d[4]), "+f"(d[5]), "+f"(d[6]), "+f"(d[7]), "+f"(d[8]), "+f"(d[9]), "+f"(d[10]), "+f"(d[11]), "+f"(d[12]), "+f"(d[13]), "+f"(d[14]), "+f"(d[15]), "+f"(d[16]), "+f"(d[17]), "+f"(d[18]), "+f"(d[19]), "+f"(d[20]), "+f"(d[21]), "+f"(d[22]), "+f"(d[23]), "+f"(d[24]), "+f"(d[25]), "+f"(d[26]), "+f"(d[27]), "+f"(d[28]), "+f"(d[29]), "+f"(d[30]), "+f"(d[31]), "+f"(d[32]), "+f"(d[33]), "+f"(d[34]), "+f"(d[35]), "+f"(d[36]), "+f"(d[37]), "+f"(d[38]), "+f"(d[39]), "+f"(d[40]), "+f"(d[41]), "+f"(d[42]), "+f"(d[43]), "+f"(d[44]), "+f"(d[45]), "+f"(d[46]), "+f"(d[47]), "+f"(d[48]), "+f"(d[49]), "+f"(d[50]), "+f"(d[51]), "+f"(d[52]), "+f"(d[53]), "+f"(d[54]), "+f"(d[55]), "+f"(d[56]), "+f"(d[57]), "+f"(d[58]), "+f"(d[59]), "+f"(d[60]), "+f"(d[61]), "+f"(d[62]), "+f"(d[63]) : "l"(da), "l"(db), "r"(sd));
}
DEV void wgmma_ss_88(float* d, u64 da, u64 db, int sd) {
  asm volatile("{\n.reg .pred p;\nsetp.ne.b32 p, %46, 0;\nwgmma.mma_async.sync.aligned.m64n88k16.f32.bf16.bf16 {%0, %1, %2, %3, %4, %5, %6, %7, %8, %9, %10, %11, %12, %13, %14, %15, %16, %17, %18, %19, %20, %21, %22, %23, %24, %25, %26, %27, %28, %29, %30, %31, %32, %33, %34, %35, %36, %37, %38, %39, %40, %41, %42, %43}, %44, %45, p, 1, 1, 0, 1;\n}\n"
    : "+f"(d[0]), "+f"(d[1]), "+f"(d[2]), "+f"(d[3]), "+f"(d[4]), "+f"(d[5]), "+f"(d[6]), "+f"(d[7]), "+f"(d[8]), "+f"(d[9]), "+f"(d[10]), "+f"(d[11]), "+f"(d[12]), "+f"(d[13]), "+f"(d[14]), "+f"(d[15]), "+f"(d[16]), "+f"(d[17]), "+f"(d[18]), "+f"(d[19]), "+f"(d[20]), "+f"(d[21]), "+f"(d[22]), "+f"(d[23]), "+f"(d[24]), "+f"(d[25]), "+f"(d[26]), "+f"(d[27]), "+f"(d[28]), "+f"(d[29]), "+f"(d[30]), "+f"(d[31]), "+f"(d[32]), "+f"(d[33]), "+f"(d[34]), "+f"(d[35]), "+f"(d[36]), "+f"(d[37]), "+f"(d[38]), "+f"(d[39]), "+f"(d[40]), "+f"(d[41]), "+f"(d[42]), "+f"(d[43]) : "l"(da), "l"(db), "r"(sd));
}
DEV void wgmma_ss_160(float* d, u64 da, u64 db, int sd) {
  asm volatile("{\n.reg .pred p;\nsetp.ne.b32 p, %82, 0;\nwgmma.mma_async.sync.aligned.m64n160k16.f32.bf16.bf16 {%0, %1, %2, %3, %4, %5, %6, %7, %8, %9, %10, %11, %12, %13, %14, %15, %16, %17, %18, %19, %20, %21, %22, %23, %24, %25, %26, %27, %28, %29, %30, %31, %32, %33, %34, %35, %36, %37, %38, %39, %40, %41, %42, %43, %44, %45, %46, %47, %48, %49, %50, %51, %52, %53, %54, %55, %56, %57, %58, %59, %60, %61, %62, %63, %64, %65, %66, %67, %68, %69, %70, %71, %72, %73, %74, %75, %76, %77, %78, %79}, %80, %81, p, 1, 1, 0, 1;\n}\n"
    : "+f"(d[0]), "+f"(d[1]), "+f"(d[2]), "+f"(d[3]), "+f"(d[4]), "+f"(d[5]), "+f"(d[6]), "+f"(d[7]), "+f"(d[8]), "+f"(d[9]), "+f"(d[10]), "+f"(d[11]), "+f"(d[12]), "+f"(d[13]), "+f"(d[14]), "+f"(d[15]), "+f"(d[16]), "+f"(d[17]), "+f"(d[18]), "+f"(d[19]), "+f"(d[20]), "+f"(d[21]), "+f"(d[22]), "+f"(d[23]), "+f"(d[24]), "+f"(d[25]), "+f"(d[26]), "+f"(d[27]), "+f"(d[28]), "+f"(d[29]), "+f"(d[30]), "+f"(d[31]), "+f"(d[32]), "+f"(d[33]), "+f"(d[34]), "+f"(d[35]), "+f"(d[36]), "+f"(d[37]), "+f"(d[38]), "+f"(d[39]), "+f"(d[40]), "+f"(d[41]), "+f"(d[42]), "+f"(d[43]), "+f"(d[44]), "+f"(d[45]), "+f"(d[46]), "+f"(d[47]), "+f"(d[48]), "+f"(d[49]), "+f"(d[50]), "+f"(d[51]), "+f"(d[52]), "+f"(d[53]), "+f"(d[54]), "+f"(d[55]), "+f"(d[56]), "+f"(d[57]), "+f"(d[58]), "+f"(d[59]), "+f"(d[60]), "+f"(d[61]), "+f"(d[62]), "+f"(d[63]), "+f"(d[64]), "+f"(d[65]), "+f"(d[66]), "+f"(d[67]), "+f"(d[68]), "+f"(d[69]), "+f"(d[70]), "+f"(d[71]), "+f"(d[72]), "+f"(d[73]), "+f"(d[74]), "+f"(d[75]), "+f"(d[76]), "+f"(d[77]), "+f"(d[78]), "+f"(d[79]) : "l"(da), "l"(db), "r"(sd));
}
template <int N> DEV void wgmma_rs(float* d, const u32* a, u64 db);
template <> DEV void wgmma_rs<256>(float* d, const u32* a, u64 db) {
  asm volatile("wgmma.mma_async.sync.aligned.m64n256k16.f32.bf16.bf16 {%0, %1, %2, %3, %4, %5, %6, %7, %8, %9, %10, %11, %12, %13, %14, %15, %16, %17, %18, %19, %20, %21, %22, %23, %24, %25, %26, %27, %28, %29, %30, %31, %32, %33, %34, %35, %36, %37, %38, %39, %40, %41, %42, %43, %44, %45, %46, %47, %48, %49, %50, %51, %52, %53, %54, %55, %56, %57, %58, %59, %60, %61, %62, %63, %64, %65, %66, %67, %68, %69, %70, %71, %72, %73, %74, %75, %76, %77, %78, %79, %80, %81, %82, %83, %84, %85, %86, %87, %88, %89, %90, %91, %92, %93, %94, %95, %96, %97, %98, %99, %100, %101, %102, %103, %104, %105, %106, %107, %108, %109, %110, %111, %112, %113, %114, %115, %116, %117, %118, %119, %120, %121, %122, %123, %124, %125, %126, %127}, {%128, %129, %130, %131}, %132, 0, 1, 1, 0;"
    : "+f"(d[0]), "+f"(d[1]), "+f"(d[2]), "+f"(d[3]), "+f"(d[4]), "+f"(d[5]), "+f"(d[6]), "+f"(d[7]), "+f"(d[8]), "+f"(d[9]), "+f"(d[10]), "+f"(d[11]), "+f"(d[12]), "+f"(d[13]), "+f"(d[14]), "+f"(d[15]), "+f"(d[16]), "+f"(d[17]), "+f"(d[18]), "+f"(d[19]), "+f"(d[20]), "+f"(d[21]), "+f"(d[22]), "+f"(d[23]), "+f"(d[24]), "+f"(d[25]), "+f"(d[26]), "+f"(d[27]), "+f"(d[28]), "+f"(d[29]), "+f"(d[30]), "+f"(d[31]), "+f"(d[32]), "+f"(d[33]), "+f"(d[34]), "+f"(d[35]), "+f"(d[36]), "+f"(d[37]), "+f"(d[38]), "+f"(d[39]), "+f"(d[40]), "+f"(d[41]), "+f"(d[42]), "+f"(d[43]), "+f"(d[44]), "+f"(d[45]), "+f"(d[46]), "+f"(d[47]), "+f"(d[48]), "+f"(d[49]), "+f"(d[50]), "+f"(d[51]), "+f"(d[52]), "+f"(d[53]), "+f"(d[54]), "+f"(d[55]), "+f"(d[56]), "+f"(d[57]), "+f"(d[58]), "+f"(d[59]), "+f"(d[60]), "+f"(d[61]), "+f"(d[62]), "+f"(d[63]), "+f"(d[64]), "+f"(d[65]), "+f"(d[66]), "+f"(d[67]), "+f"(d[68]), "+f"(d[69]), "+f"(d[70]), "+f"(d[71]), "+f"(d[72]), "+f"(d[73]), "+f"(d[74]), "+f"(d[75]), "+f"(d[76]), "+f"(d[77]), "+f"(d[78]), "+f"(d[79]), "+f"(d[80]), "+f"(d[81]), "+f"(d[82]), "+f"(d[83]), "+f"(d[84]), "+f"(d[85]), "+f"(d[86]), "+f"(d[87]), "+f"(d[88]), "+f"(d[89]), "+f"(d[90]), "+f"(d[91]), "+f"(d[92]), "+f"(d[93]), "+f"(d[94]), "+f"(d[95]), "+f"(d[96]), "+f"(d[97]), "+f"(d[98]), "+f"(d[99]), "+f"(d[100]), "+f"(d[101]), "+f"(d[102]), "+f"(d[103]), "+f"(d[104]), "+f"(d[105]), "+f"(d[106]), "+f"(d[107]), "+f"(d[108]), "+f"(d[109]), "+f"(d[110]), "+f"(d[111]), "+f"(d[112]), "+f"(d[113]), "+f"(d[114]), "+f"(d[115]), "+f"(d[116]), "+f"(d[117]), "+f"(d[118]), "+f"(d[119]), "+f"(d[120]), "+f"(d[121]), "+f"(d[122]), "+f"(d[123]), "+f"(d[124]), "+f"(d[125]), "+f"(d[126]), "+f"(d[127]) : "r"(a[0]), "r"(a[1]), "r"(a[2]), "r"(a[3]), "l"(db));
}
template <> DEV void wgmma_rs<240>(float* d, const u32* a, u64 db) {
  asm volatile("wgmma.mma_async.sync.aligned.m64n240k16.f32.bf16.bf16 {%0, %1, %2, %3, %4, %5, %6, %7, %8, %9, %10, %11, %12, %13, %14, %15, %16, %17, %18, %19, %20, %21, %22, %23, %24, %25, %26, %27, %28, %29, %30, %31, %32, %33, %34, %35, %36, %37, %38, %39, %40, %41, %42, %43, %44, %45, %46, %47, %48, %49, %50, %51, %52, %53, %54, %55, %56, %57, %58, %59, %60, %61, %62, %63, %64, %65, %66, %67, %68, %69, %70, %71, %72, %73, %74, %75, %76, %77, %78, %79, %80, %81, %82, %83, %84, %85, %86, %87, %88, %89, %90, %91, %92, %93, %94, %95, %96, %97, %98, %99, %100, %101, %102, %103, %104, %105, %106, %107, %108, %109, %110, %111, %112, %113, %114, %115, %116, %117, %118, %119}, {%120, %121, %122, %123}, %124, 1, 1, 1, 0;"
    : "+f"(d[0]), "+f"(d[1]), "+f"(d[2]), "+f"(d[3]), "+f"(d[4]), "+f"(d[5]), "+f"(d[6]), "+f"(d[7]), "+f"(d[8]), "+f"(d[9]), "+f"(d[10]), "+f"(d[11]), "+f"(d[12]), "+f"(d[13]), "+f"(d[14]), "+f"(d[15]), "+f"(d[16]), "+f"(d[17]), "+f"(d[18]), "+f"(d[19]), "+f"(d[20]), "+f"(d[21]), "+f"(d[22]), "+f"(d[23]), "+f"(d[24]), "+f"(d[25]), "+f"(d[26]), "+f"(d[27]), "+f"(d[28]), "+f"(d[29]), "+f"(d[30]), "+f"(d[31]), "+f"(d[32]), "+f"(d[33]), "+f"(d[34]), "+f"(d[35]), "+f"(d[36]), "+f"(d[37]), "+f"(d[38]), "+f"(d[39]), "+f"(d[40]), "+f"(d[41]), "+f"(d[42]), "+f"(d[43]), "+f"(d[44]), "+f"(d[45]), "+f"(d[46]), "+f"(d[47]), "+f"(d[48]), "+f"(d[49]), "+f"(d[50]), "+f"(d[51]), "+f"(d[52]), "+f"(d[53]), "+f"(d[54]), "+f"(d[55]), "+f"(d[56]), "+f"(d[57]), "+f"(d[58]), "+f"(d[59]), "+f"(d[60]), "+f"(d[61]), "+f"(d[62]), "+f"(d[63]), "+f"(d[64]), "+f"(d[65]), "+f"(d[66]), "+f"(d[67]), "+f"(d[68]), "+f"(d[69]), "+f"(d[70]), "+f"(d[71]), "+f"(d[72]), "+f"(d[73]), "+f"(d[74]), "+f"(d[75]), "+f"(d[76]), "+f"(d[77]), "+f"(d[78]), "+f"(d[79]), "+f"(d[80]), "+f"(d[81]), "+f"(d[82]), "+f"(d[83]), "+f"(d[84]), "+f"(d[85]), "+f"(d[86]), "+f"(d[87]), "+f"(d[88]), "+f"(d[89]), "+f"(d[90]), "+f"(d[91]), "+f"(d[92]), "+f"(d[93]), "+f"(d[94]), "+f"(d[95]), "+f"(d[96]), "+f"(d[97]), "+f"(d[98]), "+f"(d[99]), "+f"(d[100]), "+f"(d[101]), "+f"(d[102]), "+f"(d[103]), "+f"(d[104]), "+f"(d[105]), "+f"(d[106]), "+f"(d[107]), "+f"(d[108]), "+f"(d[109]), "+f"(d[110]), "+f"(d[111]), "+f"(d[112]), "+f"(d[113]), "+f"(d[114]), "+f"(d[115]), "+f"(d[116]), "+f"(d[117]), "+f"(d[118]), "+f"(d[119]) : "r"(a[0]), "r"(a[1]), "r"(a[2]), "r"(a[3]), "l"(db));
}
template <> DEV void wgmma_rs<224>(float* d, const u32* a, u64 db) {
  asm volatile("wgmma.mma_async.sync.aligned.m64n224k16.f32.bf16.bf16 {%0, %1, %2, %3, %4, %5, %6, %7, %8, %9, %10, %11, %12, %13, %14, %15, %16, %17, %18, %19, %20, %21, %22, %23, %24, %25, %26, %27, %28, %29, %30, %31, %32, %33, %34, %35, %36, %37, %38, %39, %40, %41, %42, %43, %44, %45, %46, %47, %48, %49, %50, %51, %52, %53, %54, %55, %56, %57, %58, %59, %60, %61, %62, %63, %64, %65, %66, %67, %68, %69, %70, %71, %72, %73, %74, %75, %76, %77, %78, %79, %80, %81, %82, %83, %84, %85, %86, %87, %88, %89, %90, %91, %92, %93, %94, %95, %96, %97, %98, %99, %100, %101, %102, %103, %104, %105, %106, %107, %108, %109, %110, %111}, {%112, %113, %114, %115}, %116, 1, 1, 1, 0;"
    : "+f"(d[0]), "+f"(d[1]), "+f"(d[2]), "+f"(d[3]), "+f"(d[4]), "+f"(d[5]), "+f"(d[6]), "+f"(d[7]), "+f"(d[8]), "+f"(d[9]), "+f"(d[10]), "+f"(d[11]), "+f"(d[12]), "+f"(d[13]), "+f"(d[14]), "+f"(d[15]), "+f"(d[16]), "+f"(d[17]), "+f"(d[18]), "+f"(d[19]), "+f"(d[20]), "+f"(d[21]), "+f"(d[22]), "+f"(d[23]), "+f"(d[24]), "+f"(d[25]), "+f"(d[26]), "+f"(d[27]), "+f"(d[28]), "+f"(d[29]), "+f"(d[30]), "+f"(d[31]), "+f"(d[32]), "+f"(d[33]), "+f"(d[34]), "+f"(d[35]), "+f"(d[36]), "+f"(d[37]), "+f"(d[38]), "+f"(d[39]), "+f"(d[40]), "+f"(d[41]), "+f"(d[42]), "+f"(d[43]), "+f"(d[44]), "+f"(d[45]), "+f"(d[46]), "+f"(d[47]), "+f"(d[48]), "+f"(d[49]), "+f"(d[50]), "+f"(d[51]), "+f"(d[52]), "+f"(d[53]), "+f"(d[54]), "+f"(d[55]), "+f"(d[56]), "+f"(d[57]), "+f"(d[58]), "+f"(d[59]), "+f"(d[60]), "+f"(d[61]), "+f"(d[62]), "+f"(d[63]), "+f"(d[64]), "+f"(d[65]), "+f"(d[66]), "+f"(d[67]), "+f"(d[68]), "+f"(d[69]), "+f"(d[70]), "+f"(d[71]), "+f"(d[72]), "+f"(d[73]), "+f"(d[74]), "+f"(d[75]), "+f"(d[76]), "+f"(d[77]), "+f"(d[78]), "+f"(d[79]), "+f"(d[80]), "+f"(d[81]), "+f"(d[82]), "+f"(d[83]), "+f"(d[84]), "+f"(d[85]), "+f"(d[86]), "+f"(d[87]), "+f"(d[88]), "+f"(d[89]), "+f"(d[90]), "+f"(d[91]), "+f"(d[92]), "+f"(d[93]), "+f"(d[94]), "+f"(d[95]), "+f"(d[96]), "+f"(d[97]), "+f"(d[98]), "+f"(d[99]), "+f"(d[100]), "+f"(d[101]), "+f"(d[102]), "+f"(d[103]), "+f"(d[104]), "+f"(d[105]), "+f"(d[106]), "+f"(d[107]), "+f"(d[108]), "+f"(d[109]), "+f"(d[110]), "+f"(d[111]) : "r"(a[0]), "r"(a[1]), "r"(a[2]), "r"(a[3]), "l"(db));
}
template <> DEV void wgmma_rs<208>(float* d, const u32* a, u64 db) {
  asm volatile("wgmma.mma_async.sync.aligned.m64n208k16.f32.bf16.bf16 {%0, %1, %2, %3, %4, %5, %6, %7, %8, %9, %10, %11, %12, %13, %14, %15, %16, %17, %18, %19, %20, %21, %22, %23, %24, %25, %26, %27, %28, %29, %30, %31, %32, %33, %34, %35, %36, %37, %38, %39, %40, %41, %42, %43, %44, %45, %46, %47, %48, %49, %50, %51, %52, %53, %54, %55, %56, %57, %58, %59, %60, %61, %62, %63, %64, %65, %66, %67, %68, %69, %70, %71, %72, %73, %74, %75, %76, %77, %78, %79, %80, %81, %82, %83, %84, %85, %86, %87, %88, %89, %90, %91, %92, %93, %94, %95, %96, %97, %98, %99, %100, %101, %102, %103}, {%104, %105, %106, %107}, %108, 1, 1, 1, 0;"
    : "+f"(d[0]), "+f"(d[1]), "+f"(d[2]), "+f"(d[3]), "+f"(d[4]), "+f"(d[5]), "+f"(d[6]), "+f"(d[7]), "+f"(d[8]), "+f"(d[9]), "+f"(d[10]), "+f"(d[11]), "+f"(d[12]), "+f"(d[13]), "+f"(d[14]), "+f"(d[15]), "+f"(d[16]), "+f"(d[17]), "+f"(d[18]), "+f"(d[19]), "+f"(d[20]), "+f"(d[21]), "+f"(d[22]), "+f"(d[23]), "+f"(d[24]), "+f"(d[25]), "+f"(d[26]), "+f"(d[27]), "+f"(d[28]), "+f"(d[29]), "+f"(d[30]), "+f"(d[31]), "+f"(d[32]), "+f"(d[33]), "+f"(d[34]), "+f"(d[35]), "+f"(d[36]), "+f"(d[37]), "+f"(d[38]), "+f"(d[39]), "+f"(d[40]), "+f"(d[41]), "+f"(d[42]), "+f"(d[43]), "+f"(d[44]), "+f"(d[45]), "+f"(d[46]), "+f"(d[47]), "+f"(d[48]), "+f"(d[49]), "+f"(d[50]), "+f"(d[51]), "+f"(d[52]), "+f"(d[53]), "+f"(d[54]), "+f"(d[55]), "+f"(d[56]), "+f"(d[57]), "+f"(d[58]), "+f"(d[59]), "+f"(d[60]), "+f"(d[61]), "+f"(d[62]), "+f"(d[63]), "+f"(d[64]), "+f"(d[65]), "+f"(d[66]), "+f"(d[67]), "+f"(d[68]), "+f"(d[69]), "+f"(d[70]), "+f"(d[71]), "+f"(d[72]), "+f"(d[73]), "+f"(d[74]), "+f"(d[75]), "+f"(d[76]), "+f"(d[77]), "+f"(d[78]), "+f"(d[79]), "+f"(d[80]), "+f"(d[81]), "+f"(d[82]), "+f"(d[83]), "+f"(d[84]), "+f"(d[85]), "+f"(d[86]), "+f"(d[87]), "+f"(d[88]), "+f"(d[89]), "+f"(d[90]), "+f"(d[91]), "+f"(d[92]), "+f"(d[93]), "+f"(d[94]), "+f"(d[95]), "+f"(d[96]), "+f"(d[97]), "+f"(d[98]), "+f"(d[99]), "+f"(d[100]), "+f"(d[101]), "+f"(d[102]), "+f"(d[103]) : "r"(a[0]), "r"(a[1]), "r"(a[2]), "r"(a[3]), "l"(db));
}
template <> DEV void wgmma_rs<192>(float* d, const u32* a, u64 db) {
  asm volatile("wgmma.mma_async.sync.aligned.m64n192k16.f32.bf16.bf16 {%0, %1, %2, %3, %4, %5, %6, %7, %8, %9, %10, %11, %12, %13, %14, %15, %16, %17, %18, %19, %20, %21, %22, %23, %24, %25, %26, %27, %28, %29, %30, %31, %32, %33, %34, %35, %36, %37, %38, %39, %40, %41, %42, %43, %44, %45, %46, %47, %48, %49, %50, %51, %52, %53, %54, %55, %56, %57, %58, %59, %60, %61, %62, %63, %64, %65, %66, %67, %68, %69, %70, %71, %72, %73, %74, %75, %76, %77, %78, %79, %80, %81, %82, %83, %84, %85, %86, %87, %88, %89, %90, %91, %92, %93, %94, %95}, {%96, %97, %98, %99}, %100, 1, 1, 1, 0;"
    : "+f"(d[0]), "+f"(d[1]), "+f"(d[2]), "+f"(d[3]), "+f"(d[4]), "+f"(d[5]), "+f"(d[6]), "+f"(d[7]), "+f"(d[8]), "+f"(d[9]), "+f"(d[10]), "+f"(d[11]), "+f"(d[12]), "+f"(d[13]), "+f"(d[14]), "+f"(d[15]), "+f"(d[16]), "+f"(d[17]), "+f"(d[18]), "+f"(d[19]), "+f"(d[20]), "+f"(d[21]), "+f"(d[22]), "+f"(d[23]), "+f"(d[24]), "+f"(d[25]), "+f"(d[26]), "+f"(d[27]), "+f"(d[28]), "+f"(d[29]), "+f"(d[30]), "+f"(d[31]), "+f"(d[32]), "+f"(d[33]), "+f"(d[34]), "+f"(d[35]), "+f"(d[36]), "+f"(d[37]), "+f"(d[38]), "+f"(d[39]), "+f"(d[40]), "+f"(d[41]), "+f"(d[42]), "+f"(d[43]), "+f"(d[44]), "+f"(d[45]), "+f"(d[46]), "+f"(d[47]), "+f"(d[48]), "+f"(d[49]), "+f"(d[50]), "+f"(d[51]), "+f"(d[52]), "+f"(d[53]), "+f"(d[54]), "+f"(d[55]), "+f"(d[56]), "+f"(d[57]), "+f"(d[58]), "+f"(d[59]), "+f"(d[60]), "+f"(d[61]), "+f"(d[62]), "+f"(d[63]), "+f"(d[64]), "+f"(d[65]), "+f"(d[66]), "+f"(d[67]), "+f"(d[68]), "+f"(d[69]), "+f"(d[70]), "+f"(d[71]), "+f"(d[72]), "+f"(d[73]), "+f"(d[74]), "+f"(d[75]), "+f"(d[76]), "+f"(d[77]), "+f"(d[78]), "+f"(d[79]), "+f"(d[80]), "+f"(d[81]), "+f"(d[82]), "+f"(d[83]), "+f"(d[84]), "+f"(d[85]), "+f"(d[86]), "+f"(d[87]), "+f"(d[88]), "+f"(d[89]), "+f"(d[90]), "+f"(d[91]), "+f"(d[92]), "+f"(d[93]), "+f"(d[94]), "+f"(d[95]) : "r"(a[0]), "r"(a[1]), "r"(a[2]), "r"(a[3]), "l"(db));
}
template <> DEV void wgmma_rs<176>(float* d, const u32* a, u64 db) {
  asm volatile("wgmma.mma_async.sync.aligned.m64n176k16.f32.bf16.bf16 {%0, %1, %2, %3, %4, %5, %6, %7, %8, %9, %10, %11, %12, %13, %14, %15, %16, %17, %18, %19, %20, %21, %22, %23, %24, %25, %26, %27, %28, %29, %30, %31, %32, %33, %34, %35, %36, %37, %38, %39, %40, %41, %42, %43, %44, %45, %46, %47, %48, %49, %50, %51, %52, %53, %54, %55, %56, %57, %58, %59, %60, %61, %62, %63, %64, %65, %66, %67, %68, %69, %70, %71, %72, %73, %74, %75, %76, %77, %78, %79, %80, %81, %82, %83, %84, %85, %86, %87}, {%88, %89, %90, %91}, %92, 1, 1, 1, 0;"
    : "+f"(d[0]), "+f"(d[1]), "+f"(d[2]), "+f"(d[3]), "+f"(d[4]), "+f"(d[5]), "+f"(d[6]), "+f"(d[7]), "+f"(d[8]), "+f"(d[9]), "+f"(d[10]), "+f"(d[11]), "+f"(d[12]), "+f"(d[13]), "+f"(d[14]), "+f"(d[15]), "+f"(d[16]), "+f"(d[17]), "+f"(d[18]), "+f"(d[19]), "+f"(d[20]), "+f"(d[21]), "+f"(d[22]), "+f"(d[23]), "+f"(d[24]), "+f"(d[25]), "+f"(d[26]), "+f"(d[27]), "+f"(d[28]), "+f"(d[29]), "+f"(d[30]), "+f"(d[31]), "+f"(d[32]), "+f"(d[33]), "+f"(d[34]), "+f"(d[35]), "+f"(d[36]), "+f"(d[37]), "+f"(d[38]), "+f"(d[39]), "+f"(d[40]), "+f"(d[41]), "+f"(d[42]), "+f"(d[43]), "+f"(d[44]), "+f"(d[45]), "+f"(d[46]), "+f"(d[47]), "+f"(d[48]), "+f"(d[49]), "+f"(d[50]), "+f"(d[51]), "+f"(d[52]), "+f"(d[53]), "+f"(d[54]), "+f"(d[55]), "+f"(d[56]), "+f"(d[57]), "+f"(d[58]), "+f"(d[59]), "+f"(d[60]), "+f"(d[61]), "+f"(d[62]), "+f"(d[63]), "+f"(d[64]), "+f"(d[65]), "+f"(d[66]), "+f"(d[67]), "+f"(d[68]), "+f"(d[69]), "+f"(d[70]), "+f"(d[71]), "+f"(d[72]), "+f"(d[73]), "+f"(d[74]), "+f"(d[75]), "+f"(d[76]), "+f"(d[77]), "+f"(d[78]), "+f"(d[79]), "+f"(d[80]), "+f"(d[81]), "+f"(d[82]), "+f"(d[83]), "+f"(d[84]), "+f"(d[85]), "+f"(d[86]), "+f"(d[87]) : "r"(a[0]), "r"(a[1]), "r"(a[2]), "r"(a[3]), "l"(db));
}
template <> DEV void wgmma_rs<160>(float* d, const u32* a, u64 db) {
  asm volatile("wgmma.mma_async.sync.aligned.m64n160k16.f32.bf16.bf16 {%0, %1, %2, %3, %4, %5, %6, %7, %8, %9, %10, %11, %12, %13, %14, %15, %16, %17, %18, %19, %20, %21, %22, %23, %24, %25, %26, %27, %28, %29, %30, %31, %32, %33, %34, %35, %36, %37, %38, %39, %40, %41, %42, %43, %44, %45, %46, %47, %48, %49, %50, %51, %52, %53, %54, %55, %56, %57, %58, %59, %60, %61, %62, %63, %64, %65, %66, %67, %68, %69, %70, %71, %72, %73, %74, %75, %76, %77, %78, %79}, {%80, %81, %82, %83}, %84, 1, 1, 1, 0;"
    : "+f"(d[0]), "+f"(d[1]), "+f"(d[2]), "+f"(d[3]), "+f"(d[4]), "+f"(d[5]), "+f"(d[6]), "+f"(d[7]), "+f"(d[8]), "+f"(d[9]), "+f"(d[10]), "+f"(d[11]), "+f"(d[12]), "+f"(d[13]), "+f"(d[14]), "+f"(d[15]), "+f"(d[16]), "+f"(d[17]), "+f"(d[18]), "+f"(d[19]), "+f"(d[20]), "+f"(d[21]), "+f"(d[22]), "+f"(d[23]), "+f"(d[24]), "+f"(d[25]), "+f"(d[26]), "+f"(d[27]), "+f"(d[28]), "+f"(d[29]), "+f"(d[30]), "+f"(d[31]), "+f"(d[32]), "+f"(d[33]), "+f"(d[34]), "+f"(d[35]), "+f"(d[36]), "+f"(d[37]), "+f"(d[38]), "+f"(d[39]), "+f"(d[40]), "+f"(d[41]), "+f"(d[42]), "+f"(d[43]), "+f"(d[44]), "+f"(d[45]), "+f"(d[46]), "+f"(d[47]), "+f"(d[48]), "+f"(d[49]), "+f"(d[50]), "+f"(d[51]), "+f"(d[52]), "+f"(d[53]), "+f"(d[54]), "+f"(d[55]), "+f"(d[56]), "+f"(d[57]), "+f"(d[58]), "+f"(d[59]), "+f"(d[60]), "+f"(d[61]), "+f"(d[62]), "+f"(d[63]), "+f"(d[64]), "+f"(d[65]), "+f"(d[66]), "+f"(d[67]), "+f"(d[68]), "+f"(d[69]), "+f"(d[70]), "+f"(d[71]), "+f"(d[72]), "+f"(d[73]), "+f"(d[74]), "+f"(d[75]), "+f"(d[76]), "+f"(d[77]), "+f"(d[78]), "+f"(d[79]) : "r"(a[0]), "r"(a[1]), "r"(a[2]), "r"(a[3]), "l"(db));
}
template <> DEV void wgmma_rs<144>(float* d, const u32* a, u64 db) {
  asm volatile("wgmma.mma_async.sync.aligned.m64n144k16.f32.bf16.bf16 {%0, %1, %2, %3, %4, %5, %6, %7, %8, %9, %10, %11, %12, %13, %14, %15, %16, %17, %18, %19, %20, %21, %22, %23, %24, %25, %26, %27, %28, %29, %30, %31, %32, %33, %34, %35, %36, %37, %38, %39, %40, %41, %42, %43, %44, %45, %46, %47, %48, %49, %50, %51, %52, %53, %54, %55, %56, %57, %58, %59, %60, %61, %62, %63, %64, %65, %66, %67, %68, %69, %70, %71}, {%72, %73, %74, %75}, %76, 1, 1, 1, 0;"
    : "+f"(d[0]), "+f"(d[1]), "+f"(d[2]), "+f"(d[3]), "+f"(d[4]), "+f"(d[5]), "+f"(d[6]), "+f"(d[7]), "+f"(d[8]), "+f"(d[9]), "+f"(d[10]), "+f"(d[11]), "+f"(d[12]), "+f"(d[13]), "+f"(d[14]), "+f"(d[15]), "+f"(d[16]), "+f"(d[17]), "+f"(d[18]), "+f"(d[19]), "+f"(d[20]), "+f"(d[21]), "+f"(d[22]), "+f"(d[23]), "+f"(d[24]), "+f"(d[25]), "+f"(d[26]), "+f"(d[27]), "+f"(d[28]), "+f"(d[29]), "+f"(d[30]), "+f"(d[31]), "+f"(d[32]), "+f"(d[33]), "+f"(d[34]), "+f"(d[35]), "+f"(d[36]), "+f"(d[37]), "+f"(d[38]), "+f"(d[39]), "+f"(d[40]), "+f"(d[41]), "+f"(d[42]), "+f"(d[43]), "+f"(d[44]), "+f"(d[45]), "+f"(d[46]), "+f"(d[47]), "+f"(d[48]), "+f"(d[49]), "+f"(d[50]), "+f"(d[51]), "+f"(d[52]), "+f"(d[53]), "+f"(d[54]), "+f"(d[55]), "+f"(d[56]), "+f"(d[57]), "+f"(d[58]), "+f"(d[59]), "+f"(d[60]), "+f"(d[61]), "+f"(d[62]), "+f"(d[63]), "+f"(d[64]), "+f"(d[65]), "+f"(d[66]), "+f"(d[67]), "+f"(d[68]), "+f"(d[69]), "+f"(d[70]), "+f"(d[71]) : "r"(a[0]), "r"(a[1]), "r"(a[2]), "r"(a[3]), "l"(db));
}
template <> DEV void wgmma_rs<128>(float* d, const u32* a, u64 db) {
  asm volatile("wgmma.mma_async.sync.aligned.m64n128k16.f32.bf16.bf16 {%0, %1, %2, %3, %4, %5, %6, %7, %8, %9, %10, %11, %12, %13, %14, %15, %16, %17, %18, %19, %20, %21, %22, %23, %24, %25, %26, %27, %28, %29, %30, %31, %32, %33, %34, %35, %36, %37, %38, %39, %40, %41, %42, %43, %44, %45, %46, %47, %48, %49, %50, %51, %52, %53, %54, %55, %56, %57, %58, %59, %60, %61, %62, %63}, {%64, %65, %66, %67}, %68, 1, 1, 1, 0;"
    : "+f"(d[0]), "+f"(d[1]), "+f"(d[2]), "+f"(d[3]), "+f"(d[4]), "+f"(d[5]), "+f"(d[6]), "+f"(d[7]), "+f"(d[8]), "+f"(d[9]), "+f"(d[10]), "+f"(d[11]), "+f"(d[12]), "+f"(d[13]), "+f"(d[14]), "+f"(d[15]), "+f"(d[16]), "+f"(d[17]), "+f"(d[18]), "+f"(d[19]), "+f"(d[20]), "+f"(d[21]), "+f"(d[22]), "+f"(d[23]), "+f"(d[24]), "+f"(d[25]), "+f"(d[26]), "+f"(d[27]), "+f"(d[28]), "+f"(d[29]), "+f"(d[30]), "+f"(d[31]), "+f"(d[32]), "+f"(d[33]), "+f"(d[34]), "+f"(d[35]), "+f"(d[36]), "+f"(d[37]), "+f"(d[38]), "+f"(d[39]), "+f"(d[40]), "+f"(d[41]), "+f"(d[42]), "+f"(d[43]), "+f"(d[44]), "+f"(d[45]), "+f"(d[46]), "+f"(d[47]), "+f"(d[48]), "+f"(d[49]), "+f"(d[50]), "+f"(d[51]), "+f"(d[52]), "+f"(d[53]), "+f"(d[54]), "+f"(d[55]), "+f"(d[56]), "+f"(d[57]), "+f"(d[58]), "+f"(d[59]), "+f"(d[60]), "+f"(d[61]), "+f"(d[62]), "+f"(d[63]) : "r"(a[0]), "r"(a[1]), "r"(a[2]), "r"(a[3]), "l"(db));
}
template <> DEV void wgmma_rs<112>(float* d, const u32* a, u64 db) {
  asm volatile("wgmma.mma_async.sync.aligned.m64n112k16.f32.bf16.bf16 {%0, %1, %2, %3, %4, %5, %6, %7, %8, %9, %10, %11, %12, %13, %14, %15, %16, %17, %18, %19, %20, %21, %22, %23, %24, %25, %26, %27, %28, %29, %30, %31, %32, %33, %34, %35, %36, %37, %38, %39, %40, %41, %42, %43, %44, %45, %46, %47, %48, %49, %50, %51, %52, %53, %54, %55}, {%56, %57, %58, %59}, %60, 1, 1, 1, 0;"
    : "+f"(d[0]), "+f"(d[1]), "+f"(d[2]), "+f"(d[3]), "+f"(d[4]), "+f"(d[5]), "+f"(d[6]), "+f"(d[7]), "+f"(d[8]), "+f"(d[9]), "+f"(d[10]), "+f"(d[11]), "+f"(d[12]), "+f"(d[13]), "+f"(d[14]), "+f"(d[15]), "+f"(d[16]), "+f"(d[17]), "+f"(d[18]), "+f"(d[19]), "+f"(d[20]), "+f"(d[21]), "+f"(d[22]), "+f"(d[23]), "+f"(d[24]), "+f"(d[25]), "+f"(d[26]), "+f"(d[27]), "+f"(d[28]), "+f"(d[29]), "+f"(d[30]), "+f"(d[31]), "+f"(d[32]), "+f"(d[33]), "+f"(d[34]), "+f"(d[35]), "+f"(d[36]), "+f"(d[37]), "+f"(d[38]), "+f"(d[39]), "+f"(d[40]), "+f"(d[41]), "+f"(d[42]), "+f"(d[43]), "+f"(d[44]), "+f"(d[45]), "+f"(d[46]), "+f"(d[47]), "+f"(d[48]), "+f"(d[49]), "+f"(d[50]), "+f"(d[51]), "+f"(d[52]), "+f"(d[53]), "+f"(d[54]), "+f"(d[55]) : "r"(a[0]), "r"(a[1]), "r"(a[2]), "r"(a[3]), "l"(db));
}
template <> DEV void wgmma_rs<96>(float* d, const u32* a, u64 db) {
  asm volatile("wgmma.mma_async.sync.aligned.m64n96k16.f32.bf16.bf16 {%0, %1, %2, %3, %4, %5, %6, %7, %8, %9, %10, %11, %12, %13, %14, %15, %16, %17, %18, %19, %20, %21, %22, %23, %24, %25, %26, %27, %28, %29, %30, %31, %32, %33, %34, %35, %36, %37, %38, %39, %40, %41, %42, %43, %44, %45, %46, %47}, {%48, %49, %50, %51}, %52, 1, 1, 1, 0;"
    : "+f"(d[0]), "+f"(d[1]), "+f"(d[2]), "+f"(d[3]), "+f"(d[4]), "+f"(d[5]), "+f"(d[6]), "+f"(d[7]), "+f"(d[8]), "+f"(d[9]), "+f"(d[10]), "+f"(d[11]), "+f"(d[12]), "+f"(d[13]), "+f"(d[14]), "+f"(d[15]), "+f"(d[16]), "+f"(d[17]), "+f"(d[18]), "+f"(d[19]), "+f"(d[20]), "+f"(d[21]), "+f"(d[22]), "+f"(d[23]), "+f"(d[24]), "+f"(d[25]), "+f"(d[26]), "+f"(d[27]), "+f"(d[28]), "+f"(d[29]), "+f"(d[30]), "+f"(d[31]), "+f"(d[32]), "+f"(d[33]), "+f"(d[34]), "+f"(d[35]), "+f"(d[36]), "+f"(d[37]), "+f"(d[38]), "+f"(d[39]), "+f"(d[40]), "+f"(d[41]), "+f"(d[42]), "+f"(d[43]), "+f"(d[44]), "+f"(d[45]), "+f"(d[46]), "+f"(d[47]) : "r"(a[0]), "r"(a[1]), "r"(a[2]), "r"(a[3]), "l"(db));
}
template <> DEV void wgmma_rs<80>(float* d, const u32* a, u64 db) {
  asm volatile("wgmma.mma_async.sync.aligned.m64n80k16.f32.bf16.bf16 {%0, %1, %2, %3, %4, %5, %6, %7, %8, %9, %10, %11, %12, %13, %14, %15, %16, %17, %18, %19, %20, %21, %22, %23, %24, %25, %26, %27, %28, %29, %30, %31, %32, %33, %34, %35, %36, %37, %38, %39}, {%40, %41, %42, %43}, %44, 1, 1, 1, 0;"
    : "+f"(d[0]), "+f"(d[1]), "+f"(d[2]), "+f"(d[3]), "+f"(d[4]), "+f"(d[5]), "+f"(d[6]), "+f"(d[7]), "+f"(d[8]), "+f"(d[9]), "+f"(d[10]), "+f"(d[11]), "+f"(d[12]), "+f"(d[13]), "+f"(d[14]), "+f"(d[15]), "+f"(d[16]), "+f"(d[17]), "+f"(d[18]), "+f"(d[19]), "+f"(d[20]), "+f"(d[21]), "+f"(d[22]), "+f"(d[23]), "+f"(d[24]), "+f"(d[25]), "+f"(d[26]), "+f"(d[27]), "+f"(d[28]), "+f"(d[29]), "+f"(d[30]), "+f"(d[31]), "+f"(d[32]), "+f"(d[33]), "+f"(d[34]), "+f"(d[35]), "+f"(d[36]), "+f"(d[37]), "+f"(d[38]), "+f"(d[39]) : "r"(a[0]), "r"(a[1]), "r"(a[2]), "r"(a[3]), "l"(db));
}
template <> DEV void wgmma_rs<64>(float* d, const u32* a, u64 db) {
  asm volatile("wgmma.mma_async.sync.aligned.m64n64k16.f32.bf16.bf16 {%0, %1, %2, %3, %4, %5, %6, %7, %8, %9, %10, %11, %12, %13, %14, %15, %16, %17, %18, %19, %20, %21, %22, %23, %24, %25, %26, %27, %28, %29, %30, %31}, {%32, %33, %34, %35}, %36, 1, 1, 1, 0;"
    : "+f"(d[0]), "+f"(d[1]), "+f"(d[2]), "+f"(d[3]), "+f"(d[4]), "+f"(d[5]), "+f"(d[6]), "+f"(d[7]), "+f"(d[8]), "+f"(d[9]), "+f"(d[10]), "+f"(d[11]), "+f"(d[12]), "+f"(d[13]), "+f"(d[14]), "+f"(d[15]), "+f"(d[16]), "+f"(d[17]), "+f"(d[18]), "+f"(d[19]), "+f"(d[20]), "+f"(d[21]), "+f"(d[22]), "+f"(d[23]), "+f"(d[24]), "+f"(d[25]), "+f"(d[26]), "+f"(d[27]), "+f"(d[28]), "+f"(d[29]), "+f"(d[30]), "+f"(d[31]) : "r"(a[0]), "r"(a[1]), "r"(a[2]), "r"(a[3]), "l"(db));
}
template <> DEV void wgmma_rs<48>(float* d, const u32* a, u64 db) {
  asm volatile("wgmma.mma_async.sync.aligned.m64n48k16.f32.bf16.bf16 {%0, %1, %2, %3, %4, %5, %6, %7, %8, %9, %10, %11, %12, %13, %14, %15, %16, %17, %18, %19, %20, %21, %22, %23}, {%24, %25, %26, %27}, %28, 1, 1, 1, 0;"
    : "+f"(d[0]), "+f"(d[1]), "+f"(d[2]), "+f"(d[3]), "+f"(d[4]), "+f"(d[5]), "+f"(d[6]), "+f"(d[7]), "+f"(d[8]), "+f"(d[9]), "+f"(d[10]), "+f"(d[11]), "+f"(d[12]), "+f"(d[13]), "+f"(d[14]), "+f"(d[15]), "+f"(d[16]), "+f"(d[17]), "+f"(d[18]), "+f"(d[19]), "+f"(d[20]), "+f"(d[21]), "+f"(d[22]), "+f"(d[23]) : "r"(a[0]), "r"(a[1]), "r"(a[2]), "r"(a[3]), "l"(db));
}
template <> DEV void wgmma_rs<32>(float* d, const u32* a, u64 db) {
  asm volatile("wgmma.mma_async.sync.aligned.m64n32k16.f32.bf16.bf16 {%0, %1, %2, %3, %4, %5, %6, %7, %8, %9, %10, %11, %12, %13, %14, %15}, {%16, %17, %18, %19}, %20, 1, 1, 1, 0;"
    : "+f"(d[0]), "+f"(d[1]), "+f"(d[2]), "+f"(d[3]), "+f"(d[4]), "+f"(d[5]), "+f"(d[6]), "+f"(d[7]), "+f"(d[8]), "+f"(d[9]), "+f"(d[10]), "+f"(d[11]), "+f"(d[12]), "+f"(d[13]), "+f"(d[14]), "+f"(d[15]) : "r"(a[0]), "r"(a[1]), "r"(a[2]), "r"(a[3]), "l"(db));
}
template <> DEV void wgmma_rs<16>(float* d, const u32* a, u64 db) {
  asm volatile("wgmma.mma_async.sync.aligned.m64n16k16.f32.bf16.bf16 {%0, %1, %2, %3, %4, %5, %6, %7}, {%8, %9, %10, %11}, %12, 1, 1, 1, 0;"
    : "+f"(d[0]), "+f"(d[1]), "+f"(d[2]), "+f"(d[3]), "+f"(d[4]), "+f"(d[5]), "+f"(d[6]), "+f"(d[7]) : "r"(a[0]), "r"(a[1]), "r"(a[2]), "r"(a[3]), "l"(db));
}

#define T_G 390
#define T_0 300
#define T_G2 300
#define A1 9
#define A2 13
#define ORDER (H4 ? 0xedcb8a957643210ull : 0xeb8dca957643210ull)
#define T_U0 4800
#define T_U1 4700
#define T_UP 1300
#define D_U 800
#define D_Y 2200
#define D_M 2000
#define D_H 1500
#define G_H 300
#define T_W 11000
#define G_W 500
#define R0 3
#define PROF0 0
#define MTOK 0
#define SWAPWG 0
#define PROMO 2
#define T_X 0
#define T_PF 400
#define T_ZS 100
#define T_P 3000
#define T_P2 3900
#define D_Z 9700
#ifndef NV
#define NV 3
#endif
#define HB 7
#define T_WO 3000
#define D_PB 0
#define T_R 3500
#define G_R 280
#define G_P 130
#define H4 0
#define RND0 0xf20
#define RND1 (H4 ? 0xf31 : 0xf431)
#define KX0 7
#define KX1 3
#define DRY 1
#define SPF 1
#define SPD 0
#define NP0 2
#define NP1 2
#define KZ0 2
#define KZ1 4
#define DKZ 2
#define TOK_S 11

template <int NW> DEV void phase_a(const Params& p, int j, int q, int role, int lane, u32 par) {
  const int o = lane & 3, cl = (8 * q + (lane >> 2)) * 2 * NW, c = 128 * j + 64 * (role & 1) + cl;
  const u32 ka = sb + j * KVP + o * 1024 + cl * 2;
  u32 sw[NW][4], k[11][NW], r[8][NW];
#pragma unroll
  for (int e = 0; e < NW; e++) lds128(sw[e], sb + SHK + c * 8 + e * 16);
#pragma unroll
  for (int i = 0; i < 11; i++) { if (NW == 2) lds64(k[i], ka + i * 128); else k[i][0] = lds32(ka + i * 128); }
#pragma unroll
  for (int i = 0; i < 8; i++) { if (NW == 2) lds64(r[i], ka + VO + i * 128); else r[i][0] = lds32(ka + VO + i * 128); }
  u16* dst = p.s->u + c * 2048 + 2040 - 32 * (role >> 1) - 8 * o;
#pragma unroll
  for (int e = 0; e < NW; e++) {
    const u32 w0 = prmt(sw[e][0], sw[e][2], 0x5410), w1 = prmt(sw[e][0], sw[e][2], 0x7632), w2 = prmt(sw[e][1], sw[e][3], 0x5410), w3 = prmt(sw[e][1], sw[e][3], 0x7632);
#pragma unroll
    for (int i = 0; i < 8; i++) r[i][e] = hmul2(hfma2(k[i + 3][e], w0, hfma2(k[i + 2][e], w1, hfma2(k[i + 1][e], w2, hmul2(k[i][e], w3)))), r[i][e]);
    r[7][e] = tagw(r[7][e], (o & 1) * 0x10001u, par);
    stg128(dst + e * 4096, make_uint4(prmt(r[7][e], r[6][e], 0x5410), prmt(r[5][e], r[4][e], 0x5410), prmt(r[3][e], r[2][e], 0x5410), prmt(r[1][e], r[0][e], 0x5410)));
    stg128(dst + e * 4096 + 2048, make_uint4(prmt(r[7][e], r[6][e], 0x7632), prmt(r[5][e], r[4][e], 0x7632), prmt(r[3][e], r[2][e], 0x7632), prmt(r[1][e], r[0][e], 0x7632)));
  }
}
template <int N, int STRIDE> DEV void shift_copy(u32 a, u32 dv, bool first) {
  uint4 w[N]; u32 pv[N];
#pragma unroll
  for (int i = 0; i < N; i++) { w[i] = lds128(a + i * STRIDE); pv[i] = lds32(a + i * STRIDE - 4); }
  if (first) { w[0].x = hadd2(w[0].x, dv); sts32(a, w[0].x); }
#pragma unroll
  for (int i = 0; i < N; i++)
    sts128(a + KO + i * STRIDE, make_uint4(prmt(pv[i], w[i].x, 0x5432), prmt(w[i].x, w[i].y, 0x5432), prmt(w[i].y, w[i].z, 0x5432), prmt(w[i].z, w[i].w, 0x5432)));
}
template <int S0, int S1> DEV void load_a(u32* a, u32 p) {
#pragma unroll
  for (int s = S0; s < S1; s++) { a[4 * s] = lds32(p + 256 * s); a[4 * s + 1] = lds32(p + 256 * s + 128); a[4 * s + 2] = lds32(p + 256 * s + 16); a[4 * s + 3] = lds32(p + 256 * s + 144); }
}
template <int S> DEV void load_a_if(u32* a, u32 p, bool c) {
  asm volatile("{\n.reg .pred q;\nsetp.ne.u32 q, %5, 0;\n@q ld.shared.b32 %0, [%4+%6];\n@q ld.shared.b32 %1, [%4+%7];\n@q ld.shared.b32 %2, [%4+%8];\n@q ld.shared.b32 %3, [%4+%9];\n}\n"
               : "+r"(a[4 * S]), "+r"(a[4 * S + 1]), "+r"(a[4 * S + 2]), "+r"(a[4 * S + 3])
               : "r"(p), "r"((u32)c), "n"(256 * S), "n"(256 * S + 128), "n"(256 * S + 16), "n"(256 * S + 144) : "memory");
}
template <int K> DEV void conv_pair(float* d, const u32* a, u32 lo) {
  wgmma_rs<256 - 32 * K>(d, a + 8 * K, desc_join(lo + 32 * K, 8u));
  wgmma_rs<240 - 32 * K>(d, a + 8 * K + 4, desc_join(lo + 32 * K + 16, 8u));
  wg_commit();
}
template <int K> DEV void conv_work(const float* d, u32* a, u32 ps, u32 pn, bool more) {
  constexpr int I = 7 - K;
  u32 pk[4];
  if constexpr (K >= R0) load_a_if<2 * (K - R0)>(a, pn, more);
#pragma unroll
  for (int e = 0; e < 4; e++) {
    const int nb = 4 * I + e;
    pk[e] = nb < 31 ? pack2(d[4 * nb] + d[(4 * nb + 6) & 127], d[4 * nb + 1] + d[(4 * nb + 7) & 127]) : pack2(d[4 * nb], d[4 * nb + 1]);
  }
  stsm4t(ps - 512 * I, pk);
  if constexpr (K >= R0) load_a_if<2 * (K - R0) + 1>(a, pn, more);
}
template <int NB> DEV int validate(u32 dst, const void* src, u32 bytes, bool fetched, u32 rbar, u32& rph, u32 off, u32 old) {
  int n = 0;
#pragma unroll 1
  while (true) {
    if (!fetched) { e_xload(dst, src, bytes, rbar); mbar_wait(rbar, rph); rph ^= 1; PROF(threadIdx.x == 288 && bytes > 12000, 122 + (bytes > 13000)); }
    fetched = false;
    u32 m = 1;
    const u32 a0 = dst + off, lim = a0 + bytes - 1024;
#pragma unroll 1
    for (u32 a = a0; a <= lim; a += NB * 1024) {
      u32 v[NB];
#pragma unroll
      for (int i = 0; i < NB; i++) v[i] = lds32(i < 4 ? a + i * 1024 : min(a + i * 1024, lim));
#pragma unroll
      for (int i = 0; i < NB; i += 2) m &= (v[i] ^ old) & (v[i + 1] ^ old);
    }
    if (__all_sync(0xffffffffu, m != 0)) break;
    trap_if_gt(++n, 1 << 16);
    RST(bytes >> 10);
  }
  return n;
}
DEV void ln_post(float (*c)[4], u32 a, int lane) {
  const bool o = lane & 4;
  if ((lane & 3) == (lane >> 3)) sts128(a, make_uint4(__float_as_uint(c[0][0]), __float_as_uint(o ? c[1][1] : c[1][0]), __float_as_uint(c[0][2]), __float_as_uint(o ? c[2][3] : c[2][2])));
}
DEV void ln_params(u32 a, u32* r2, u32* n2) {
  u32 v[8][4];
#pragma unroll
  for (int i = 0; i < 8; i++) lds128(v[i], a + i * 128);
#pragma unroll
  for (int hh = 0; hh < 2; hh++) {
    auto sum = [&](int e) { return ((__uint_as_float(v[0][e]) + __uint_as_float(v[1][e])) + (__uint_as_float(v[2][e]) + __uint_as_float(v[3][e]))) +
                                   ((__uint_as_float(v[4][e]) + __uint_as_float(v[5][e])) + (__uint_as_float(v[6][e]) + __uint_as_float(v[7][e]))); };
    const float mu = sum(2 * hh) * (1.f / 640.f), rs = rsqrtf(fmaxf(sum(2 * hh + 1) * (1.f / 640.f) - mu * mu, 0.f) + 1e-5f);
    r2[hh] = pack2(rs, rs); n2[hh] = pack2(-mu * rs, -mu * rs);
  }
}
DEV void fetch_y(const Maps& tm, int j0, int j1, int role) {
  e_expect(bar(B_YF + (j0 >> 1)), 4096 * (j1 - j0));
#pragma unroll 1
  for (int j = j0; j < j1; j++) e_tma2d(sb + YS + j * 4096, &tm.y, bar(B_YF + (j0 >> 1)), 16 * (role & 3), (role >> 2) * 640 + 128 * j);
}
DEV float gelu2(float a) { return fmaf(a, tanh_fast(a * fmaf(0.035677408136300125f, a * a, 0.7978845608028654f)), a); }

template <int N>
DEV void g1_pass(float* acc, u32* zp, const u32* x1, int pass, int t128, u32* z2p, u32* xp, u32 ep) {
  constexpr int NG = N / 8, WG = N == 88, NPART = WG ? NP1 : NP0, PART = (NG + NPART - 1) / NPART, K0 = WG ? KZ1 : KZ0;
  constexpr u32 LB0 = WG ? desc_lo(sb + 16384, 1408) : desc_lo(sb, 8192), SIDE = (NPART == 2 ? 1 + (1 << DKZ) : 1) << K0;
  const int lane = t128 & 31;
  const u32 stop = pass ? 512 + SIDE : 512 + (1 << (WG ? KX1 : KX0));
  u32 la = desc_lo(sb + XR, 1024), lb = LB0, bf = bar(B_FULL), bv = bar(B_VAL), par = 0, bprev = bar(B_DUMMY), kb = 0;
#pragma unroll 1
  do {
    bool go;
    mbar_wait(bv & ~7u, 0);
    mbar_wait(bf, par);
    PROF(kb == 0 && t128 == 0, WG ? 109 + pass : 40 + pass);
#pragma unroll 1
    do {
      auto mma = [&](int q) {
        if constexpr (WG) wgmma_ss_88(acc, desc_join(la + q * 128, 8u), desc_join(lb + q * 176, 8u), kb | q);
        else wgmma_ss_128(acc, desc_join(la + q * 128, 8u), desc_join(lb + q * 128, 0x40000040u), kb | q);
      };
      PROFG(t128 == 0 && pass == PG1, 1 + 10 * WG + 32 - __clz(kb));
      wg_fence();
      mma(0); mma(1);
      const u32 bcur = bf + 8 * (B_EMPTY - B_FULL);
      kb = max(2 * kb, 1u);
      const bool wrap = kb == 16;
      par ^= wrap; bf = wrap ? bar(B_FULL) : bf + 8; bv += 4;
      go = __all_sync(0xffffffffu, mbar_test(bf, par) & mbar_test(bv & ~7u, 0) & !(kb & stop));
      mma(2); mma(3);
      wg_commit();
      la += 512; lb = wrap ? LB0 : lb + (BT >> 4);
      wg_wait<1>();
      mbar_arrive_if(bprev, t128 == 0);
      bprev = bcur;
    } while (go);
    if (kb & stop & 511) {
      const int c = (lane + 2 * (t128 >> 5)) & 7;
      auto put = [&](int pt) {
#pragma unroll
        for (int n = pt * PART; n < (pt + 1) * PART && n < NG; n++) {
          const int gq = N == 128 ? 4 + n : n < 4 ? n : 16 + n;
          stg32(z2p + gq * 32, tagw(zp[2 * n], c == (gq & 7), ~ep));
          stg32(z2p + (27 + gq) * 32, tagw(zp[2 * n + 1], c == ((gq + 3) & 7), ~ep));
        }
        if (pt == NPART - 1) { __syncwarp(); mbar_arrive_if(bar(B_Z2D), lane == 0); PROF(t128 == 0, 107 + WG); }
      };
      if (pass == 0) {
#pragma unroll
        for (int i = 0; i < 20; i++) stg32(xp + (16 * (i >> 2) + ((i >> 1) & 1)) * 256 + (i & 1) * 32, x1[i]);
      } else if (kb == 1 << K0) {
        mbar_wait(bar(B_ZS), 0);
        PROF(t128 == 0, WG ? 47 : 106);
        const u32 zsp = sb + M_ZS + (t128 >> 5) * 64 + (lane & 28), v0 = lds32(zsp), v1 = lds32(zsp + 32);
        const u32 r0 = prmt(v0, v0, 0x1010), n0 = prmt(v0, v0, 0x3232), r1 = prmt(v1, v1, 0x1010), n1 = prmt(v1, v1, 0x3232);
#pragma unroll
        for (int n = 0; n < NG; n++) { zp[2 * n] = hfma2(zp[2 * n], r0, n0); zp[2 * n + 1] = hfma2(zp[2 * n + 1], r1, n1); }
        put(0);
      } else if (NPART == 2) put(1);
    }
  } while (kb != 512);
  wg_wait<0>();
  mbar_arrive_if(bprev, t128 == 0);
  PROF(t128 == 0, WG ? 111 + pass : 43 + pass);
}
template <int N>
DEV void g2_pass(float* acc, bool elect) {
  constexpr u32 ha = 0x40000040u, hb = 8;
  u32 s = 5, la = desc_lo(sb + AR, 16), lb = desc_lo(sb + 5 * BT + (N == 128 ? 0 : 2048), 3456), bf = bar(B_FULL + 5), bv = bar(B_ZV), par = 0, bprev = bar(B_DUMMY), k = 0;
#pragma unroll 1
  do {
    bool go;
    mbar_wait(bv, 0);
    mbar_wait(bf, par);
    PROF(k == 0 && elect && N == 128, 42);
#pragma unroll 1
    do {
      auto mma = [&](int q) {
        if constexpr (N == 128) wgmma_ss_128(acc, desc_join(la + q * 2, ha), desc_join(lb + q * 432, hb), k | q);
        else wgmma_ss_88(acc, desc_join(la + q * 2, ha), desc_join(lb + q * 432, hb), k | q);
      };
      wg_fence();
      mma(0); mma(1);
      const u32 inc = s == 5 ? -5 : 1, bcur = bf + 8 * (B_EMPTY - B_FULL);
      par ^= s == 4; bf += 8 * inc; bv = min(bv + 8, bar(B_ZV + NV - 1)); k++;
      go = __all_sync(0xffffffffu, mbar_test(bf, par) & mbar_test(bv, 0) & (k < 32));
      mma(2); mma(3);
      wg_commit();
      la += s == 4 ? -5 * 512 : 512; lb += inc * (BT >> 4); s += inc;
      wg_wait<1>();
      mbar_arrive_if(bprev, elect);
      bprev = bcur;
    } while (go);
  } while (k < 32);
  wg_wait<0>();
}

DEV void spare_cta(const Params& p, const Maps& tm, int cq, int tid, int warp) {
  const int lane = tid & 31, kr = lane & 7, lg = lane >> 3, seg = warp % 3, kq = warp / 3;
  const u32 br = sb + M_BAR;
  e_init(br + 8 * warp, 1); e_init(br + 96 + 8 * warp, 1);
  const u32 ep = ld_rlx32(p.s->ctr);
  __syncthreads();
#define SPROF(i)
  until(clock(), SPD);
  auto release = [&](int f) {
    __syncthreads();
    if (tid == 0) { fence_gpu(); ctr_arrive(p.s->ctr, f, ep, tid); }
    SPROF(10 + f);
    __syncthreads();
  };
  const int ro = (cq & 1) * 3 + (cq >> 1) * 2 + lg, bx = seg < 2 ? seg : 2 + (ro >> 2), ck = seg < 2 ? lg : ro & 3;
#pragma unroll 1
  for (int pass = 0; pass < 2; pass++) {
    const int c0 = (pass ? 0 : 864) + 192 * cq;
    if (warp == 0) {
#pragma unroll 1
      for (int i = 0; i < 20; i++) {
        if ((i & 3) == 0) e_expect(br + 40 * pass + 2 * i, 32768);
        e_tma2d(sb + i * 8192, &tm.win32, br + 40 * pass + 8 * (i >> 2), (i & 2) ? c0 - 192 * cq + 768 + 32 * ((cq >> 1) + (i & 1)) : c0 + ((i & 1) ? 160 : 128 * pass), 128 * (i >> 2));
      }
    }
#pragma unroll 1
    for (int i = 0; i < 5; i++) {
      mbar_wait(br + 40 * pass + 8 * i, 0);
      SPROF(5 * pass + i);
      if (warp == 1 && SPF == 0) { e_pf3d(&tm.win, c0 + 32 - 32 * pass, 128 * i); e_pf3d(&tm.win, c0 + 32 - 32 * pass, 128 * i + 64); }
      if (seg < 2 || lg < 3) {
        uint4 v[4];
#pragma unroll
        for (int e = 0; e < 4; e++) v[e] = lds128(sb + i * 32768 + bx * 8192 + ((4 * e + kq) * 8 + kr) * 64 + ((ck ^ (kr >> 1)) << 4));
#pragma unroll
        for (int e = 0; e < 4; e++) stg128(p.s->ws + (((pass * 4 + cq) * 80 + 16 * i + 4 * e + kq) * 11 + seg * 4 + lg) * 64 + kr * 8, v[e]);
      }
    }
    if (warp == 1 && SPF == 1)
      for (int i = 0; i < 10; i++) e_pf3d(&tm.win, c0 + 32 - 32 * pass, 64 * i);
    release(I_WS + pass);
  }
  auto fetch = [&](int r) {
    const int c2 = (cq + r) & 3;
    e_expect(br + 96 + 8 * r, 69120);
#pragma unroll 1
    for (int e = 0; e < 9; e++) e_tma2d(sb + (r % 3) * 69120 + e * 7680, &tm.wout, br + 96 + 8 * r, 160 * cq, e < 8 ? 192 * c2 + 24 * e : 768 + 24 * c2);
  };
  if (warp == 0) { fetch(0); fetch(1); fetch(2); }
#pragma unroll 1
  for (int r = 0; r < 4; r++) {
    mbar_wait(br + 96 + 8 * r, 0);
    SPROF(13 + (r >> 1));
#pragma unroll 1
    for (int u = warp * 4 + lg; u < 135; u += 48) {
      const int gm = u / 5, be = u % 5, ps = gm < 6 || gm > 21 ? gm : gm < 16 ? gm + 6 : gm - 10, kg = r == 0 ? ps : ps < 12 ? 15 + 12 * r + ps : 36 + 15 * r + ps;
      const u32 a = sb + (r % 3) * 69120 + (gm * 8 + kr) * 320 + be * 64;
      const uint4 v0 = lds128(a), v1 = lds128(a + 16), v2 = lds128(a + 32), v3 = lds128(a + 48);
      u16* dst = p.s->wo + (cq * 540 + kg * 5 + be) * 256 + kr * 8;
      stg128(dst, make_uint4(v0.x, v1.x, v2.x, v3.x));
      stg128(dst + 64, make_uint4(v0.y, v1.y, v2.y, v3.y));
      stg128(dst + 128, make_uint4(v0.z, v1.z, v2.z, v3.z));
      stg128(dst + 192, make_uint4(v0.w, v1.w, v2.w, v3.w));
    }
    if (r == 0) { __syncthreads(); if (warp == 0) fetch(3); }
  }
  release(I_WO);
}

__global__ void __launch_bounds__(384, 1) mega_kernel(const __grid_constant__ Params p, const __grid_constant__ Maps tm) {
  extern __shared__ __align__(1024) unsigned char smem_raw[];
  const u32 t_start = clock();
  const int tid = threadIdx.x, warp = __shfl_sync(0xffffffffu, tid >> 5, 0), lane = tid & 31;
  int role;
  {
    u32 sm; asm volatile("mov.u32 %0, %%smid;" : "=r"(sm));
    const u32 x = sm - 64, q = (x * 4682u) >> 16;
    const u32 lo = ((sm + 14) & 14) * 8 + (sm >> 4) * 2, hi = ((x - 14 * q) & 14) * 8 + 8 + 2 * q;
    role = sm >= 124 ? sm - 4 : sm >= 120 ? sm + 8 : (sm < 64 ? lo : hi) + (sm & 1);
    role = __shfl_sync(0xffffffffu, role, 0);
  }
  if (role >= 128) { trap_if_gt(smem_u32(smem_raw) ^ sb, 0); spare_cta(p, tm, role - 128, tid, warp); return; }
  const int rt = role >> 2, cq = role & 3;

  e_init(bar(48 + warp), 2);
  if (warp == 8) {
    e_expect(bar(B_KV), KVP);
    e_tma2d(sb, &tm.k, bar(B_KV), 64 * (role & 1), 32 * (role >> 1) - 3);
    e_tma2d(sb + VO, &tm.v, bar(B_KV), 64 * (role & 1), 32 * (role >> 1));
    e_xload(sb + SHK, p.shk, 5120, bar(B_KV));
    PROF(lane == 0, 0);
  }
  if (warp < 6) e_tmpf(&tm.ssm + warp);
  e_init6(bar(warp), (u32)(0x111111a88882ull >> (4 * warp)) & 15);
  if (warp == 8) { e_expect(bar(B_SS), 4096); e_tma2d(sb + kslot(0), &tm.ssm, bar(B_SS), 0, 8 * role); PROF(lane == 0, 98); }
  if (tid < 63) {
    sts128(sb + (tid < 5 ? US + tid * UP + 4096 : tid < 15 ? kslot((tid - 5) >> 1) - 16 + (tid & 1) * KO : PWB + ((tid - 15) & 7) * PWP + ((tid - 15) >> 3) * 16), make_uint4(0, 0, 0, 0));
    fence_async_smem();
  }
  __syncthreads();

  if (warp < 8) {
    asm volatile("setmaxnreg.inc.sync.aligned.u32 224;");
    u32 dv;
    asm volatile("ld.global.nc.u16 %0, [%1];" : "=r"(dv) : "l"(p.ssmD + (tid & 128) + role));
    u32 ep = ld_rlx32(p.s->ctr);
    const int wg = warp >> 2, w = warp & 3, t128 = tid & 127, g = lane >> 2, t = lane & 3;
    const bool elect = t128 == 0;
    const u32 ts = __shfl_sync(0xffffffffu, t_start, 0);
    PROF(tid == 0, 1);
    {
      const u32 koff = sb + ((g & 1) ? 0 : KO) + 4 * (t + (g >> 1) - 3) + 32 * w;
      const u32 pw = sb + PWB + wg * 4 * PWP;
      u32 a[64];
      ep = __shfl_sync(0xffffffffu, ep, 0);
      consume(dv);
      if (wg) mbar_wait(bar(B_KV), 0);
#pragma unroll 1
      for (u32 js = wg ? RND1 : RND0; js != 15; js >>= 4) {
        const int j = js & 15;
        mbar_wait(bar(B_KV + j), 0);
        PROF(elect, j < 2 ? 2 + j : j == 2 ? 91 : j == 3 ? 126 : 93);
        phase_a<1>(p, j, w, role, lane_now(), (ep & 1) - 1);
        PROF(elect, j < 2 ? 4 + j : j == 2 ? 90 : j == 3 ? 127 : 79);
        if (j < 2) {
          mbar_wait(bar(B_SS + wg), 0);
          shift_copy<2, 2048>(sb + kslot(wg) + t128 * 16, dv, elect);
          bsync(1 + wg, 128);
          load_a<0, 16>(a, koff + kslot(wg));
          PROFD(elect, 6 + wg, a[63]);
        }
      }
#pragma unroll 1
      for (int ch = wg; ch < 5; ch += 2) {
        float d[128];
        const u32 pn = koff + kslot(ch + 2), ps = pw + w * (PWP + 32) + (255 - lane_now()) * 16, lo = desc_lo(sb + US + ch * UP, 16);
        const bool more = ch < 3;
        mbar_wait(bar(B_UV + ch), 0);
        if (MTOK) mbar_wait(bar(B_TOK + wg), ((ch + 1) >> 1 & 1) ^ 1); else if (ch > 0) bsync(3 + wg, 256);
        if (ch == 4) stamp_post(p.s->ctr, ep, S_Y, ts, lane_now() + w);
        PROF(elect, 8 + ch);
        wg_fence();
        conv_pair<0>(d, a, lo); conv_pair<1>(d, a, lo); conv_pair<2>(d, a, lo);
        if (R0 == 0 && more) mbar_wait(bar(B_KB + ch), 0);
        wg_wait<2>();
        mbar_arrive_if(bar(B_EMPTY) + 8 * (ch == 1 ? w >> 1 : ch - 1), w < ((H4 ? 0x12020 : 0x12040) >> (4 * ch) & 7) && lane_now() == 0);
        conv_work<0>(d, a, ps, pn, more); conv_pair<3>(d, a, lo);
        if (R0 == 1 && more) mbar_wait(bar(B_KB + ch), 0);
        wg_wait<2>(); conv_work<1>(d, a, ps, pn, more); conv_pair<4>(d, a, lo);
        if (R0 == 2 && more) mbar_wait(bar(B_KB + ch), 0);
        wg_wait<2>(); conv_work<2>(d, a, ps, pn, more); conv_pair<5>(d, a, lo); conv_pair<6>(d, a, lo); conv_pair<7>(d, a, lo);
        if (MTOK) mbar_arrive_if(bar(B_TOK + 1 - wg), elect); else if (ch < 4) barrive(4 - wg, 256);
        if (R0 == 3 && more) mbar_wait(bar(B_KB + ch), 0);
        wg_wait<2>(); conv_work<3>(d, a, ps, pn, more); conv_work<4>(d, a, ps, pn, more); conv_work<5>(d, a, ps, pn, more);
        wg_wait<0>();
        PROFD(elect, 13 + ch, __float_as_uint(d[0]));
        conv_work<6>(d, a, ps, pn, more); conv_work<7>(d, a, ps, pn, more);
        bsync(1 + wg, 128);
        u32 q[2][4][4];
        const int t128 = 32 * w + lane_now();
#pragma unroll
        for (int h = 0; h < 2; h++)
#pragma unroll
          for (int i = 0; i < 4; i++) lds128(q[h][i], pw + i * PWP + h * 2048 + t128 * 16);
        if (more) load_a<16 - 2 * R0, 16>(a, pn);
        u16* yp = p.s->y + ((t128 >> 3) * 640 + 128 * ch + role) * 64 + ((t128 & 7) << 3);
#pragma unroll
        for (int h = 0; h < 2; h++) {
          u32 y[4];
#pragma unroll
          for (int e = 0; e < 4; e++) y[e] = hadd2(hadd2(q[h][0][e], q[h][1][e]), hadd2(q[h][2][e], q[h][3][e]));
          stg128(yp + h * (16 * 640 * 64), make_uint4(tagw(y[0], ~t128 & 1, ~ep), y[1], y[2], y[3]));
        }
        PROF(elect, 18 + ch);
      }
    }
    u32 zp[32], x1[5][4];
    u32* hp = (u32*)p.s->h2 + ((rt * 80 + 2 * warp) * 8 + 2 * cq) * 32 + lane;
    const u32 bs0 = hmul2((u32)__ldg(p.bsp + rt * 64 + 16 * w + g) * 0x10001u, 0x3f003f00u), bs1 = hmul2((u32)__ldg(p.bsp + rt * 64 + 16 * w + g + 8) * 0x10001u, 0x3f003f00u);
    {
      u32 x[5][4], S[5][2], C[5][2], r2[2], n2[2];
      float c[3][4];
      const u32 xa = sb + QS + wg * 2048 + (lane & 15) * 128 + (((2 * w + (lane >> 4)) ^ (lane & 7)) << 4);
      const u32 ya = sb + YS + (16 * warp + (lane >> 4) * 8 + (lane & 7)) * 32 + ((((lane >> 3) ^ (lane >> 2)) & 1) << 4);
      const u32 ma = sb + M_MOD + 64 * (warp >> 1) + 16 * t + 8 * (warp & 1), la = sb + M_LN + g * 16, par = (ep & 1) - 1;
      auto clear = [&]() {
#pragma unroll
        for (int i = 0; i < 12; i++) c[i >> 2][i & 3] = 0.f;
      };
      stg32((u32*)p.s->stz + role * 256 + tid, ep);
      mbar_wait(bar(B_Q), 0);
      PROF(elect, 23 + wg);
#pragma unroll
      for (int j = 0; j < 5; j++) ldsm4(x[j], xa + j * 4096);
      clear();
#pragma unroll
      for (int j = 0; j < 5; j++) row_stats(c, x[j]);
      ln_post(c, la + warp * 128, lane);
      bsync(5, 256);
      ln_params(la, r2, n2);
      PROFD(elect, 25 + wg, r2[0]);
#pragma unroll 1
      for (u32 ph = 0;; ph++) {
        u32 T[5][4], m = 1, bad = 0;
        mbar_wait(bar(B_YF + 2), ph & 1);
        PROF(elect && wg == 0 && ph == 0, 88);
#pragma unroll
        for (int j = 0; j < 5; j++) {
          u32 A[2], B[2], G[2];
          lds64(B, ma + j * 256); lds64(A, ma + j * 256 + 1280); lds64(G, ma + j * 256 + 2560); lds64(S[j], ma + j * 256 + 3840); lds64(C[j], ma + j * 256 + 5120);
#pragma unroll
          for (int i = 0; i < 2; i++) {
            m = min(min(min(m, A[i]), min(B[i], G[i])), min(S[j][i], C[j][i]));
            A[i] = hmul2(G[i], hadd2(A[i], ONE2)); B[i] = hmul2(G[i], B[i]); C[j][i] = hadd2(C[j][i], ONE2);
          }
#pragma unroll
          for (int i = 0; i < 4; i++) T[j][i] = hfma2(hfma2(x[j][i], r2[i & 1], n2[i & 1]), A[i >> 1], B[i >> 1]);
        }
        clear();
#pragma unroll
        for (int j = 0; j < 5; j++) {
          u32 y[4];
          if (j == 3) PROFD(elect && ph == 0, 27 + wg, __float_as_uint(c[2][0]));
          if (j == 0 || j == 3) mbar_wait(bar(B_YF + (j >> 1)), ph & 1);
          if (j == 3) tile_post(p.s->ctr + 32 + 32 * rt + cq, ts, ep, tid == 0);
          if (j == 0 || j == 3) PROF(elect && wg == 0 && ph == 0, 89 + j);
          ldsm4t(y, ya + j * 4096);
          bad |= (y[0] ^ par) | (y[2] ^ par);
#pragma unroll
          for (int i = 0; i < 4; i++) x1[j][i] = hfma2(y[i], T[j][i], x[j][i]);
          row_stats(c, x1[j]);
        }
        ln_post(c, la + 1024 + warp * 128, lane);
        PROFV(elect, 96, 100 * ph + 100);
        if (__all_sync(0xffffffffu, bsync_and(5, 256, m != 0 && (g != 0 || (bad & 0x10001) == 0)))) break;
        trap_if_gt(ph, 1 << 16);
        RST(__any_sync(0xffffffffu, m == 0) ? 1 : __any_sync(0xffffffffu, g == 0 && (bad & 0x10001)) ? 2 : 0);
        if (warp == 0) { fetch_y(tm, 0, 3, role); fetch_y(tm, 3, 5, role); e_xload(sb + M_MOD, p.s->mod, 6400, bar(B_YF + 2)); }
      }
      mbar_arrive_if(bar(B_HD), lane == 0);
      ln_params(la + 1024, r2, n2);
      PROFD(elect, 29 + wg, r2[0]);
      const u32 m0 = (lane & 7) == 2 * cq, m1 = (lane & 7) == 2 * cq + 1;
#pragma unroll
      for (int j = 0; j < 5; j++) {
#pragma unroll
        for (int i = 0; i < 4; i++)
          stg32(hp + (16 * j + (i >> 1)) * 256 + (i & 1) * 32, tagw(hfma2(hfma2(x1[j][i], r2[i & 1], n2[i & 1]), C[j][i >> 1], S[j][i >> 1]), (i & 1) ? m1 : m0, par));
        if ((HB >> j) & 1) bsync(5, 256);
      }
      PROF(elect, 31 + wg);
    }
    const int vg = wg ^ SWAPWG;
    float z[64];
#pragma unroll
    for (int i = 0; i < 64; i++) asm volatile("" : "=f"(z[i]));
    u32* z2p = (u32*)p.s->z2 + (role * 8 + 2 * w) * 27 * 32 + lane;
#pragma unroll 1
    for (int pass = -DRY; pass < 2; pass++) {
      if (pass < 0) {}
      else if (vg == 0) g1_pass<128>(z, zp, x1[0], pass, t128, z2p, hp + 32 * 80 * 8 * 32, ep);
      else g1_pass<88>(z, zp, x1[0], pass, t128, z2p, hp + 32 * 80 * 8 * 32, ep);
      float st[4] = {0.f, 0.f, 0.f, 0.f};
      auto act = [&](int n0, int n1) {
#pragma unroll
        for (int i = 2 * n0; i < 2 * n1; i++) {
          const float u0 = gelu2(z[2 * i]), u1 = gelu2(z[2 * i + 1]);
          zp[i] = pack2(u0, u1);
          st[2 * (i & 1)] += u0 + u1; st[2 * (i & 1) + 1] = fmaf(u1, u1, fmaf(u0, u0, st[2 * (i & 1) + 1]));
        }
      };
      if (vg == 0) act(11, 16);
      act(0, 11);
      if (pass == 0) {
        const bool up = t & 2;
        float a = (up ? st[2] : st[0]) + shx(up ? st[0] : st[2], 2), q = (up ? st[3] : st[1]) + shx(up ? st[1] : st[3], 2);
        a += shx(a, 1); q += shx(q, 1);
        if (!(t & 1))
          asm volatile("st.relaxed.gpu.global.v2.b32 [%0], {%1,%2};" ::"l"(p.s->stz + (role * 64 + 16 * w + g + 4 * t) * 2 + vg), "f"(a), "r"(prmt(__float_as_uint(q), ep + 1, 0x3214)) : "memory");
        __syncwarp();
        mbar_arrive_if(bar(B_ZP), lane == 0);
      }
      PROFD(elect && pass >= 0, 113 + 2 * pass + vg, zp[21]);
    }
    if (vg == 0) g2_pass<128>(z, elect); else g2_pass<88>(z, elect);
    PROFD(elect && vg == 0, 45, __float_as_uint(z[0]));
    {
      u32* Pp = (u32*)p.s->P + ((role * 27 + 6 * vg) * 8 + 2 * w) * 32 + lane;
      u32* Pq = Pp + (6 + 4 * vg) * 256;
      const u32 Ps = sb + ((6 * vg + (lane >> 4)) * 8 + 2 * w) * 128 + (lane & 15) * 16, Pt = Ps + (6 + 4 * vg) * 1024;
      const u32 m0 = (lane & 7) == 2 * w, m1 = (lane & 7) == 2 * w + 1;
      auto gate = [&](int n0, int n1) {
#pragma unroll
        for (int n = n0; n < n1; n++) {
          zp[2 * n] = tagw(hmul2(zp[2 * n], hfma2(pack2(z[4 * n], z[4 * n + 1]), 0x3f003f00u, bs0)), m0, ~ep);
          zp[2 * n + 1] = tagw(hmul2(zp[2 * n + 1], hfma2(pack2(z[4 * n + 2], z[4 * n + 3]), 0x3f003f00u, bs1)), m1, ~ep);
          if (n < 6) { stg32(Pp + n * 256, zp[2 * n]); stg32(Pp + n * 256 + 32, zp[2 * n + 1]); }
        }
      };
      auto put = [&](int n0, int n1) {
#pragma unroll
        for (int n = n0; n < n1; n++) { stg32(Pq + n * 256, zp[2 * n]); stg32(Pq + n * 256 + 32, zp[2 * n + 1]); }
      };
      gate(0, 11);
      if (vg == 0) gate(11, 16);
      bsync(5, 256);
      mbar_arrive_if(bar(B_PD), lane == 0);
#pragma unroll
      for (int n = 0; n < 10; n += 2) stsm4((n < 6 ? Ps : Pt) + n * 1024, zp + 2 * n);
      if (vg == 0) {
#pragma unroll
        for (int n = 10; n < 16; n += 2) stsm4(Pt + n * 1024, zp + 2 * n);
        fence_async_smem();
        barrive(5, 256);
        until(clock(), D_PB);
        __syncwarp();
        put(6, 16);
      } else {
        stsm2(sb + XR + 2 * w * 128 + (lane & 15) * 16, zp[20], zp[21]);
        fence_async_smem();
        put(6, 11);
      }
    }
    if (vg) {
      bsync(5, 256);
      PROF(elect, 48);
      float o[80];
      u32 la = desc_lo(sb, 1024), lb = desc_lo(sb + BT, 2560), bf = bar(B_WF), bprev = bar(B_DUMMY), s7 = 0, par = 0, bv = bar(B_PV), res[60];
#pragma unroll 1
      for (int i = 0; i < 17; i++) {
        if ((0xa550 >> i) & 1) { mbar_wait(bv, 0); bv += 8; PROF(elect && (i == 4 || i == 10), 49 + i / 6); }
        mbar_wait(bf, par);
        wg_fence();
        wgmma_ss_160(o, desc_join(la, 8u), desc_join(lb, 8u), i);
        la += i == 4 ? (XR >> 4) - 12 * 128 : 128;
        wgmma_ss_160(o, desc_join(la, 8u), desc_join(lb + 320, 8u), 1);
        wgmma_ss_160(o, desc_join(la + 128, 8u), desc_join(lb + 640, 8u), 1);
        wg_commit();
        la += 256;
        wg_wait<1>();
        mbar_arrive_if(bprev, elect);
        bprev = bf + 8 * (B_WE - B_WF);
        const bool wrap = s7 == 6;
        s7 = wrap ? 0 : s7 + 1; par ^= wrap; bf += wrap ? -48 : 8; lb += wrap ? -6 * (int)(WOST >> 4) : (int)(WOST >> 4);
      }
      PROF(elect, 120);
      mbar_wait(bar(B_RES), 0);
      mbar_wait(bar(B_WF + 3), 0);
      PROF(elect, 51);
      const u32 ra = sb + (t * 8 + 2 * w) * 128 + g * 16;
      wg_fence();
#pragma unroll
      for (int q = 0; q < 3; q++) wgmma_ss_160(o, desc_join(desc_lo(sb + XR + (38 + q) * 2048, 1024), 8u), desc_join(desc_lo(sb + BT + 3 * WOST + q * 5120, 2560), 8u), 1);
      wg_commit();
#pragma unroll
      for (int e = 0; e < 15; e++) {
        const int i = e / 3 * 2 + e % 3 - 1;
        if (e % 3) lds128(res + 4 * i, ra + (i >> 1) * 4096 + (i & 1) * 128); else lds128(res + 40 + 4 * (e / 3), sb + 20480 + (e / 3) * 64 + t * 16);
      }
      wg_wait<0>();
      PROFD(elect, 52, __float_as_uint(o[0]));
      u16* op = p.out + (rt * 64 + 16 * w + g) * 640 + 160 * cq + 8 * t;
#pragma unroll
      for (int i = 0; i < 10; i++) {
        const int be = i >> 1, h = i & 1;
        u32 r[4];
#pragma unroll
        for (int e = 0; e < 4; e++) r[e] = hfma2(pack2(o[16 * be + 4 * e + 2 * h], o[16 * be + 4 * e + 2 * h + 1]), res[40 + 4 * be + e], res[4 * i + e]);
        stg128(op + h * 8 * 640 + 32 * be, make_uint4(r[0], r[1], r[2], r[3]));
      }
      PROF(elect, 53);
    }
  } else {
    asm volatile("setmaxnreg.dec.sync.aligned.u32 56;");
    const int hw = warp - 8;
    if (hw == 0) {
      {
        const int n = lane < 15 ? (int)(ORDER >> (4 * lane)) & 15 : lane, j = n < 15 ? (n * 11) >> 5 : n < 20 ? n - 15 : n - 20, ty = n < 15 ? n - 3 * j : n < 20 ? 3 : 4;
        const int c0 = ty < 2 ? 128 * j + 64 * (role & 1) : ty == 2 ? 0 : ty == 3 ? 32 * role : 64 * j;
        const int c1 = ty < 2 ? 32 * (role >> 1) - 3 + 3 * ty : ty == 2 ? 1024 * j + 8 * role : ty == 3 ? 128 * j : 16 * role;
        const u32 dst = sb + (ty < 2 ? j * KVP + ty * VO : ty == 2 ? kslot(j) : ty == 3 ? WM + j * 8192 : QS + j * 2048);
        const u32 br = bar(ty < 2 ? B_KV + j : ty == 2 ? B_SS + j : ty == 3 ? B_WM + j : B_Q), bytes = ty == 0 ? VO : ty < 3 ? 4096 : ty == 3 ? 8192 : 2048;
        int due = T_0 + 3 * T_G;
#pragma unroll 1
        for (int i = 3; i < 30; i++) {
          until(t_start, due);
          if (lane == i) xtma2d(dst, &tm.k + ty, br, c0, c1, bytes);
          PROF(lane == i && (i < 4 || i == 29), 96 + lane);
          due += i < 15 ? T_G + (i == 14 ? T_X : 0) : i < 20 ? 2 * T_G2 : T_G2 / 2;
          __syncwarp();
        }
      }
      const u32 ep = ld_rlx32(p.s->ctr);
      int tz = 0;
      {
        ctr_poll(p.s->ctr, I_WS, ep, 4);
        PROF(lane == 0, 33);
        const u16* src = p.s->ws + cq * 56320;
#pragma unroll 1
        for (int r = 0; r < 4; r++) {
          if (r == 2) { mbar_wait(bar(B_WS1), 0); tz = lds32(sb + M_TZ); src += 3 * 56320; }
#pragma unroll 1
          for (int s = 0; s < 5; s++, src += 5632) {
            if (r == 0) until(t_start, T_W + s * G_W);
            w_g1(bar(B_EMPTY) + 8 * s, r & 1, bar(B_FULL) + 8 * s, sb + s * BT, &tm.win, (r < 2 ? 896 : 0) + 192 * cq, 64 * s + 320 * (r & 1), src);
            PROF(lane == 0 && r == 0, 74 + s); PROFG(lane == 0 && r == 2 * PG1 + 1, 21 + s);
          }
        }
      }
      mbar_wait(bar(B_Z2D), 0);
      fence_gpu();
      ctr_arrive(p.s->ctr, I_Z2, ep, lane);
      PROF(lane == 0, 36);
      until(t_start, tz + D_Z);
      PROF(lane == 0, 35);
      {
        const u16* src = p.s->z2 + cq * (BT / 2);
        u32 par = 0;
#pragma unroll 1
        for (int c0 = 0;; par ^= 1) {
#pragma unroll
          for (int e = 0; e < 6; e++, c0 += 64, src += 2 * BT) {
            const int s = (e + 5) % 6;
            if (e == 2 && c0 == 2048) break;
            w_g2(bar(B_EMPTY + s), e ? par : par ^ 1, bar(B_FULL + s), sb + s * BT, src, sb + AR + e * 8192, &tm.wsp, c0, 64 * rt);
            if (e == NV - 1 && c0 < 384) { ctr_poll(p.s->ctr, I_Z2, ep, 128); PROF(lane == 0, 37); }
          }
          if (c0 == 2048) break;
        }
      }
      if (role == 0 && lane < 9) p.s->ctr[lane ? 15 - 8 * (ep & 1) + lane : 0] = lane ? 0 : ep + 1;
      if (role < 100 && lane < 16) stg32((u32*)p.s->mod + role * 16 + lane, 0);
      mbar_wait(bar(B_WO), 0);
      {
        const u16* src = p.s->wo + cq * 18 * (WOST / 2);
#pragma unroll 1
        for (int i = 0; i < 7; i++, src += WOST / 2) {
          w_load<WOST>(bar(B_EMPTY + 1) + 8 * ((i + 1) >> 1), 1, bar(B_WF) + 8 * i, sb + BT + i * WOST, src);
          stamp_post(p.s->ctr, ep, S_P, t_start, lane + i);
        }
        int due = stamp_wait(p.s->ctr, ep, S_P) + T_R;
#pragma unroll 1
        for (int r = 0; r < 2; r++) {
#pragma unroll 1
          for (int i = 0; i < 7 - 3 * r; i++, src += WOST / 2, due += G_R) { until(t_start, due); w_load<WOST>(bar(B_WE) + 8 * i, r, bar(B_WF) + 8 * i, sb + BT + i * WOST, src); }
          if (r == 0) { e_expect(bar(B_RES), 20800); e_load(sb, p.s->x1 + role * 10240, 20480, bar(B_RES)); e_load(sb + 20480, p.s->mod + 3200 + 160 * cq, 320, bar(B_RES)); }
        }
      }
    } else {
      u32 rph = 0, ep = ld_rlx32(p.s->ctr);
      if (hw == 1) {
        tile_wait(p.s->ctr + 32 + 32 * rt, ep - 1);
#pragma unroll 1
        for (int j = 0; j < 5; j++) {
          const int due = j ? T_U1 + j * T_UP : T_U0;
          until(t_start, due - D_U);
          if (!__all_sync(0xffffffffu, mbar_test(bar(B_KV + j), 0))) { mbar_wait(bar(B_KV + j), 0); until(clock(), D_U); }
          until(t_start, due);
          PROF(lane == 0, j ? 53 + j : 38);
          const int n = validate<4>(sb + US + j * UP, p.s->u + (128 * j + role) * 2048, 4096, false, bar(B_RF), rph, lane * 32, ep);
          if (n) RST(j ? j > 1 ? 3 + j : 3 : 10);
          e_arrive(bar(B_UV + j));
          PROF(lane == 0, 64 + j); PROFV(lane == 0, 69 + j, 100 * n + 100);
        }
        mbar_wait(bar(B_EMPTY + 3), 0);
        const int ty = stamp_wait(p.s->ctr, ep, S_Y);
        fetch_y(tm, 0, 3, role);
        PROF(lane == 0, 58);
        until(t_start, ty + D_Y);
        fetch_y(tm, 3, 5, role);
        PROF(lane == 0, 59);
        {
          mbar_wait(bar(B_YF + 1), 0);
          const u32 t0 = t_start + tile_wait(p.s->ctr + 32 + 32 * rt, ep);
          mbar_wait(bar(B_HD), 0);
#pragma unroll 1
          for (int j = 0; j < 5; j++) {
            until(t0, D_H + j * G_H);
            e_xload(sb + XR + j * 16384, p.s->h2 + (rt * 5 + j) * 8192, 16384, bar(B_SS + j));
            PROF(lane == 0 && j == 0, 60);
          }
        }
        const u32 t0 = clock();
#pragma unroll 1
        for (int i = 0; i < 16; i++) { until(t0, i * T_PF); e_prefetch(p.wsp + (role * 16 + i) * 2048, 4096); }
      } else {
        const int hi = hw - 2;
        const u32 ts = __shfl_sync(0xffffffffu, t_start, 0);
        const u32 d0 = __ldg(p.ssmD + 128 * min(lane, 4) + role);
        {
          const int ht = tid - 320, g = lane >> 2, t = lane & 3;
          u32 cv[5];
#pragma unroll
          for (int i = 0; i < 5; i++) cv[i] = __ldg((const u32*)p.c + ht + 64 * i);
#pragma unroll 1
          for (int i = 0; i < 5; i++) {
            const float a = bflo(cv[0]), b = bfhi(cv[0]);
            const u32 v = pack2(__fdividef(a, 1.f + __expf(-a)), __fdividef(b, 1.f + __expf(-b))), ad = sb + M_SC + i * 256 + hi * 128 + t * 32 + g * 2;
            sts16(ad, v); sts16(ad + 16, v >> 16);
#pragma unroll
            for (int j = 0; j < 4; j++) cv[j] = cv[j + 1];
          }
          sts32(sb + M_D + 4 * min(lane, 4), d0);
          __syncwarp();
        }
        ep = __shfl_sync(0xffffffffu, ep, 0);
        mbar_wait(bar(B_KV), 0);
#pragma unroll 1
        for (int j = 2; j < 5; j++) {
          const int lane = lane_now(), ht = 32 * hi + lane;
          if (H4 && j == 4) {
            mbar_wait(bar(B_KV + 4), 0);
            PROF(ht == 0, 93);
            phase_a<2>(p, 4, hi, role, lane, (opaque(ep) & 1) - 1);
            __syncwarp();
            e_arrive(bar(B_EMPTY + 1));
            PROF(ht == 0, 79);
          }
          mbar_wait(bar(B_SS + j), 0);
          shift_copy<4, 1024>(sb + kslot(j) + hi * 512 + lane_now() * 16, lds32(sb + M_D + 4 * j), hi + lane_now() == 0);
          __syncwarp();
          e_arrive(bar(B_KB + j - 2));
          PROF(ht == 0, 78 + j);
        }
        const int lane = lane_now(), ht = 32 * hi + lane, g = lane >> 2;
        {
          float acc[8] = {0.f, 0.f, 0.f, 0.f, 0.f, 0.f, 0.f, 0.f};
#pragma unroll 1
          for (int j = 0; j < 5; j++) {
            u32 cv[4], wv[8][4];
            mbar_wait(bar(B_WM + j), 0);
            if (j == 4) stamp_post(p.s->ctr, ep, S_MOD, ts, ht);
            PROF(ht == 0, 83 + j);
            lds128(cv, sb + M_SC + j * 256 + hi * 128 + g * 16);
#pragma unroll
            for (int i = 0; i < 8; i++) lds128(wv[i], sb + WM + j * 8192 + hi * 4096 + i * 512 + lane * 16);
#pragma unroll
            for (int i = 0; i < 8; i++) {
              const float c = (i & 1) ? bfhi(cv[i >> 1]) : bflo(cv[i >> 1]);
#pragma unroll
              for (int e = 0; e < 4; e++) { acc[2 * e] = fmaf(bflo(wv[i][e]), c, acc[2 * e]); acc[2 * e + 1] = fmaf(bfhi(wv[i][e]), c, acc[2 * e + 1]); }
            }
          }
          const u32 pa = sb + WM + hi * 4096;
          sts128(pa + lane * 32, make_uint4(__float_as_uint(acc[0]), __float_as_uint(acc[1]), __float_as_uint(acc[2]), __float_as_uint(acc[3])));
          sts128(pa + lane * 32 + 16, make_uint4(__float_as_uint(acc[4]), __float_as_uint(acc[5]), __float_as_uint(acc[6]), __float_as_uint(acc[7])));
          bsync(6, 64);
          if (ht < 16) {
            float s[4] = {0.f, 0.f, 0.f, 0.f};
            const u32 ra = sb + WM + (role < 100 ? (ht & 3) * 32 + (ht >> 2) * 8 : ht * 8);
#pragma unroll
            for (int i = 0; i < 16; i++) { u32 v[2]; lds64(v, ra + (i >> 3) * 4096 + (i & 7) * 128); s[i & 2] += __uint_as_float(v[0]); s[(i & 2) + 1] += __uint_as_float(v[1]); }
            stg32((u32*)p.s->mod + role * 16 + ht, nz(pack2(s[0] + s[2], s[1] + s[3])));
          }
          __syncwarp();
          mbar_arrive_if(bar(B_EMPTY + 3), ht == 0);
          PROF(ht == 0, 39);
        }
        if (hi == 0) {
          until(ts, stamp_wait(p.s->ctr, ep, S_MOD) + D_M);
          PROF(lane == 0, 95);
          e_xload(sb + M_MOD, p.s->mod, 6400, bar(B_YF + 2));
        }
#pragma unroll 1
        for (int i = 0; i < 5; i++) {
          mbar_wait(bar(B_SS + i), 1);
          PROF(ht == 0 && i == 0, 61);
          const int n = validate<8>(sb + XR + i * 16384 + hi * 8192, p.s->h2 + (rt * 5 + i) * 8192 + hi * 4096, 8192, true, bar(B_RF + hw - 1), rph, lane * 32 + g * 4, ep);
          e_arrive(bar(B_VAL + i));
          if (i == 0) { e_arrive(bar(B_EMPTY + 4)); stamp_post(p.s->ctr, ep, S_Z, ts, ht); }
          PROF(ht == 0 && (i == 0 || i == 4), i ? 63 : 62); PROFV(ht == 0 && n, 97, 100 * i + 100);
        }
        if (hi == 0) ctr_poll(p.s->ctr, I_WS + 1, ep, 4); else sts32(sb + M_TZ, stamp_wait(p.s->ctr, ep, S_Z));
        e_arrive(bar(B_WS1));
        PROF(lane == 0, hi ? 119 : 34);
        {
          mbar_wait(bar(B_ZP), 0);
          until(clock(), T_ZS);
          float s, q;
          int n = 0;
#pragma unroll 1
          while (true) {
            uint4 v[4];
            u32 bad = 0;
#pragma unroll
            for (int i = 0; i < 4; i++) v[i] = ld_rlx128(p.s->stz + ((rt * 4 + i) * 64 + ht) * 2);
            s = 0.f; q = 0.f;
#pragma unroll
            for (int i = 0; i < 4; i++) {
              bad |= (v[i].y ^ (ep + 1)) | (v[i].w ^ (ep + 1));
              s += __uint_as_float(v[i].x) + __uint_as_float(v[i].z); q += __uint_as_float(v[i].y) + __uint_as_float(v[i].w);
            }
            if (__all_sync(0xffffffffu, (bad & 255) == 0)) break;
            trap_if_gt(++n, 1 << 20);
          }
          const float mu = s * (1.f / 864.f), rs = rsqrtf(fmaxf(q * (1.f / 864.f) - mu * mu, 0.f) + 4e-5f);
          sts32(sb + M_ZS + ht * 4, pack2(rs, -mu * rs));
          __syncwarp();
          e_arrive(bar(B_ZS));
        }
      }
#pragma unroll 1
      for (int i = 0, s = 5; i < NV; i++) {
        mbar_wait(bar(B_FULL) + 8 * s, 0);
        PROF(hw == 1 && lane == 0 && i == 0, 117);
        const int n = validate<10>(sb + s * BT + (hw - 1) * 9216, p.s->z2 + (i * 4 + cq) * (BT / 2) + (hw - 1) * 4608, 9216, true, bar(B_RF + hw - 1), rph, lane_now() * 33 & ~3, ep);
        e_arrive(bar(B_ZV) + 8 * i);
        PROFV(lane == 0 && n, 118, 100 * i + 100);
        s = s == 5 ? 0 : s + 1;
      }
      if (hw == 1) { until(clock(), T_WO); ctr_poll(p.s->ctr, I_WO, ep, 4); e_arrive(bar(B_WO)); PROF(lane == 0, 94); }
      mbar_wait(bar(B_WF), 0);
      const int tp = stamp_wait(p.s->ctr, ep, S_P);
      mbar_wait(bar(B_PD), 0);
#pragma unroll 1
      for (int i = 0; i < 2; i++) {
        const u32 bytes = i ? 15360 : 12288;
        until(t_start, tp + (i ? T_P2 : T_P) + ((cq + hw) & 3) * G_P);
        PROF(hw == 1 && lane == 0, 100 + 2 * i);
        const int n = validate<8>(sb + XR + 1024 + i * 36864 + (hw - 1) * bytes, p.s->P + (rt * 4 + ((cq + hw) & 3)) * (BT / 2) + i * 6144, bytes, false,
                                  bar(B_RF + hw - 1), rph, lane_now() * 33 & ~3, ep);
        e_arrive(bar(B_PV + 3 * i) + 8 * (hw - 1));
        PROF(hw == 1 && lane == 0, 101 + 2 * i); PROFV(hw == 1 && lane == 0, 104 + i, 100 * n + 100);
      }
    }
  }
}

typedef CUresult (*EncodeFn)(CUtensorMap*, CUtensorMapDataType, cuuint32_t, void*, const cuuint64_t*, const cuuint64_t*, const cuuint32_t*,
                             const cuuint32_t*, CUtensorMapInterleave, CUtensorMapSwizzle, CUtensorMapL2promotion, CUtensorMapFloatOOBfill);

extern "C" void kernel_launch(void* const* d_in, const int* in_sizes, int n_in, void* d_out, int out_size) {
  static EncodeFn enc = nullptr;
  if (!enc) {
    void* fn = nullptr; cudaDriverEntryPointQueryResult st;
    cudaGetDriverEntryPoint("cuTensorMapEncodeTiled", &fn, cudaEnableDefault, &st);
    enc = (EncodeFn)fn;
    cudaFuncSetAttribute(mega_kernel, cudaFuncAttributeMaxDynamicSharedMemorySize, SMEM_BYTES);
  }
  Params p;
  p.shk = (const u16*)d_in[3]; p.ssmD = (const u16*)d_in[5];
  p.wsp = (const u16*)d_in[8]; p.bsp = (const u16*)d_in[9]; p.c = (const u16*)d_in[11];
  p.out = (u16*)d_out;
  cudaGetSymbolAddress((void**)&p.s, g_s);
  auto mk = [&](void* base, int rank, cuuint64_t d0, cuuint64_t d1, cuuint32_t b0, cuuint32_t b1, CUtensorMapSwizzle sw) {
    CUtensorMap m;
    cuuint64_t gd[3] = {d0, d1, 2}, gs[2] = {d0 * 2, 128};
    cuuint32_t bd[3] = {b0, b1, 2}, es[3] = {1, 1, 1};
    enc(&m, CU_TENSOR_MAP_DATA_TYPE_BFLOAT16, rank, base, gd, gs, bd, es, CU_TENSOR_MAP_INTERLEAVE_NONE, sw, (CUtensorMapL2promotion)PROMO,
        CU_TENSOR_MAP_FLOAT_OOB_FILL_NONE);
    return m;
  };
  Maps tm;
  tm.k = mk(d_in[1], 2, 640, 2048, 64, 35, CU_TENSOR_MAP_SWIZZLE_NONE);
  tm.v = mk(d_in[2], 2, 640, 2048, 64, 32, CU_TENSOR_MAP_SWIZZLE_NONE);
  tm.ssm = mk(d_in[4], 2, 256, 5120, 256, 8, CU_TENSOR_MAP_SWIZZLE_NONE);
  tm.wmod = mk(d_in[12], 2, 3840, 640, 32, 128, CU_TENSOR_MAP_SWIZZLE_NONE);
  tm.q = mk(d_in[0], 2, 640, 2048, 64, 16, CU_TENSOR_MAP_SWIZZLE_128B);
  tm.win = mk(d_in[7], 3, 1728, 640, 64, 64, CU_TENSOR_MAP_SWIZZLE_128B);
  tm.wsp = mk(d_in[8], 2, 2048, 2048, 64, 64, CU_TENSOR_MAP_SWIZZLE_128B);
  tm.y = mk(p.s->y, 2, 64, 20480, 16, 128, CU_TENSOR_MAP_SWIZZLE_32B);
  tm.win32 = mk(d_in[7], 2, 1728, 640, 32, 128, CU_TENSOR_MAP_SWIZZLE_64B);
  tm.wout = mk(d_in[10], 2, 640, 864, 160, 24, CU_TENSOR_MAP_SWIZZLE_NONE);
  mega_kernel<<<132, 384, SMEM_BYTES>>>(p, tm);
}
```

```cpp
#include <cuda_runtime.h>
#include <cuda.h>
#include <cuda_bf16.h>
#include <stdint.h>

typedef uint16_t u16; typedef uint32_t u32; typedef unsigned long long u64;
#define DEV __device__ __forceinline__

struct Scratch {
  u32 ctr[1280];
  u16 mod[4096];
  u64 stz[128 * 64 * 2];
  u16 u[640 * 2048];
  u16 y[32 * 640 * 64];
  u16 h2[32 * 80 * 8 * 64];
  u16 x1[32 * 80 * 8 * 64];
  u16 ws[2 * 4 * 80 * 11 * 64];
  u16 wo[4 * 108 * 20 * 64];
  u16 z2[32 * 4 * 8 * 27 * 64];
  u16 P[32 * 4 * 27 * 8 * 64];
};
__device__ __align__(1024) Scratch g_s;
enum { I_WS = 0, I_WO = 2, I_Z2 = 3 };
enum { S_Y = 0, S_MOD = 1, S_Z = 2, S_P = 3 };

struct Maps { CUtensorMap k, v, ssm, wmod, q, win, wsp, y, win32, wout; };
struct Params {
  Scratch* s;
  const u16 *shk, *ssmD, *c, *wsp, *bsp;
  u16* out;
};

constexpr u32 sb = 1024;
constexpr u32 BT = 27648, XR = 5 * BT, AR = 6 * BT, MISC = XR + 81920, SMEM_BYTES = 232448;
constexpr u32 M_LN = MISC, M_BAR = MISC + 2048, M_MOD = M_BAR + 1024, M_ZS = M_MOD + 7680, M_SM = M_ZS + 256, M_PROF = M_SM + 256;
constexpr u32 M_SC = M_MOD, M_TZ = M_SM, M_D = M_SM + 16;
constexpr u32 US = XR, UP = 4224, PWB = US + 5 * UP, PWP = 4192, YR = 2 * BT, KP = 8320, KO = 4144, WM = YR + 41984;
constexpr u32 KVP = 8576, VO = 4480, SHK = 5 * KVP, YS = XR - 20480, QS = XR + 55296, WOST = 15360, RES = AR + 16384;
DEV u32 kslot(int j) { return YR + 128 + j * KP; }
enum { B_WM = 0, B_RF = 5, B_SS = 8, B_PV = 13, B_YF = 19, B_RES = 22, B_FULL = 23, B_WO = 29, B_RD = 30, B_WF = 33, B_WE = 40,
       B_VAL = 48, B_KB = 53, B_KV = 56, B_EMPTY = 61, B_WS1 = 67, B_ZS = 71,
       B_DUMMY = 72, B_HD = 73, B_ZP = 74, B_PD = 75, B_Z2D = 76, B_Q = 77, B_UV = 78,
       B_ZV = 84 };
DEV constexpr u32 bar(int i) { return sb + M_BAR + 8 * i; }

#define RST(i)
#define PROF(cond, i)
#define PROFD(cond, i, dep)
#define PROFV(cond, i, v)
#define PROFG(cond, i)

DEV u32 smem_u32(const void* p) { return (u32)__cvta_generic_to_shared(p); }
DEV void wg_fence() { asm volatile("wgmma.fence.sync.aligned;" ::: "memory"); }
DEV void wg_commit() { asm volatile("wgmma.commit_group.sync.aligned;" ::: "memory"); }
template <int N> DEV void wg_wait() { asm volatile("wgmma.wait_group.sync.aligned %0;" ::"n"(N) : "memory"); }
DEV u64 desc_join(u32 lo, u32 hi) { return ((u64)hi << 32) | lo; }
DEV constexpr u32 desc_lo(u32 addr, u32 lbo) { return ((addr & 0x3FFFF) >> 4) | ((lbo >> 4) << 16); }
DEV void mbar_init(u32 bar, int cnt) { asm volatile("mbarrier.init.shared::cta.b64 [%0], %1;" ::"r"(bar), "r"(cnt) : "memory"); }
DEV void mbar_arrive(u32 bar) { asm volatile("mbarrier.arrive.shared::cta.b64 _, [%0];" ::"r"(bar) : "memory"); }
DEV void mbar_arrive_if(u32 bar, bool c) { asm volatile("{\n.reg .pred p;\nsetp.ne.u32 p, %1, 0;\n@p mbarrier.arrive.shared::cta.b64 _, [%0];\n}\n" ::"r"(bar), "r"((u32)c) : "memory"); }
#define SAFE 0
#define SPIN(body) "W_LOOP:\n" body "@!p bra W_LOOP;\n"
DEV void mbar_wait(u32 bar, u32 parity) {
  asm volatile("{\n.reg .pred p, q;\n.reg .u32 n;\n" SPIN("mbarrier.try_wait.parity.shared::cta.b64 p, [%0], %1;\n") "}\n" ::"r"(bar), "r"(parity) : "memory");
}
DEV bool mbar_test(u32 bar, u32 parity) {
  u32 ok;
  asm volatile("{\n.reg .pred p;\nmbarrier.test_wait.parity.shared::cta.b64 p, [%1], %2;\nselp.u32 %0, 1, 0, p;\n}\n" : "=r"(ok) : "r"(bar), "r"(parity) : "memory");
  return ok;
}
DEV void trap_if_gt(int n, int lim) { asm volatile("{\n.reg .pred p;\nsetp.gt.s32 p, %0, %1;\n@p st.shared.u32 [%2], %0;\n}\n" ::"r"(n), "r"(lim), "r"(0x400000) : "memory"); }
DEV void until(u32 t0, int c) { while ((int)(clock() - t0) < c) {} }
DEV void bsync(int id, int n) { asm volatile("bar.sync %0, %1;" ::"r"(id), "r"(n) : "memory"); }
DEV bool bsync_and(int id, int n, bool v) {
  u32 r;
  asm volatile("{\n.reg .pred p, q;\nsetp.ne.u32 p, %3, 0;\nbarrier.red.and.aligned.pred q, %1, %2, p;\nselp.u32 %0, 1, 0, q;\n}\n" : "=r"(r) : "r"(id), "r"(n), "r"((u32)v) : "memory");
  return r;
}
DEV void barrive(int id, int n) { asm volatile("bar.arrive %0, %1;" ::"r"(id), "r"(n) : "memory"); }
DEV void fence_async_smem() { asm volatile("fence.proxy.async.shared::cta;" ::: "memory"); }
DEV void fence_gpu() { asm volatile("fence.acq_rel.gpu;" ::: "memory"); }
#define ELECT "{\n.reg .pred p;\nelect.sync _|p, 0xffffffff;\n"
DEV void e_init(u32 bar, int cnt) { asm volatile(ELECT "@p mbarrier.init.shared::cta.b64 [%0], %1;\n}\n" ::"r"(bar), "r"(cnt) : "memory"); }
DEV void e_init6(u32 b, int cnt) {
  asm volatile(ELECT "@p mbarrier.init.shared::cta.b64 [%0], 1;\n@p mbarrier.init.shared::cta.b64 [%0+96], 1;\n@p mbarrier.init.shared::cta.b64 [%0+192], 1;\n"
               "@p mbarrier.init.shared::cta.b64 [%0+288], 1;\n@p mbarrier.init.shared::cta.b64 [%0+480], 2;\n@p mbarrier.init.shared::cta.b64 [%0+576], %1;\n@p mbarrier.init.shared::cta.b64 [%0+672], 3;\n}\n" ::"r"(b), "r"(cnt) : "memory");
}
DEV void e_expect(u32 bar, u32 bytes) { asm volatile(ELECT "@p mbarrier.arrive.expect_tx.shared::cta.b64 _, [%0], %1;\n}\n" ::"r"(bar), "r"(bytes) : "memory"); }
DEV void e_arrive(u32 bar) { asm volatile(ELECT "@p mbarrier.arrive.shared::cta.b64 _, [%0];\n}\n" ::"r"(bar) : "memory"); }
DEV void e_load(u32 dst, const void* src, u32 bytes, u32 bar) {
  asm volatile(ELECT "@p cp.async.bulk.shared::cluster.global.mbarrier::complete_tx::bytes [%0], [%1], %2, [%3];\n}\n" ::"r"(dst), "l"(src), "r"(bytes), "r"(bar) : "memory");
}
DEV void e_xload(u32 dst, const void* src, u32 bytes, u32 bar) {
  asm volatile(ELECT "@p mbarrier.arrive.expect_tx.shared::cta.b64 _, [%3], %2;\n@p cp.async.bulk.shared::cluster.global.mbarrier::complete_tx::bytes [%0], [%1], %2, [%3];\n}\n"
               ::"r"(dst), "l"(src), "r"(bytes), "r"(bar) : "memory");
}
DEV void e_tma2d(u32 dst, const void* tm, u32 bar, int c0, int c1) {
  asm volatile(ELECT "@p cp.async.bulk.tensor.2d.shared::cluster.global.mbarrier::complete_tx::bytes [%0], [%1, {%3, %4}], [%2];\n}\n" ::"r"(dst), "l"(tm), "r"(bar), "r"(c0), "r"(c1) : "memory");
}
DEV void e_tma3d(u32 dst, const void* tm, u32 bar, int c0, int c1) {
  asm volatile(ELECT "@p cp.async.bulk.tensor.3d.shared::cluster.global.mbarrier::complete_tx::bytes [%0], [%1, {%3, %4, %5}], [%2];\n}\n" ::"r"(dst), "l"(tm), "r"(bar), "r"(c0), "r"(c1), "r"(0) : "memory");
}
DEV void e_pf3d(const void* tm, int c0, int c1) {
  asm volatile(ELECT "@p cp.async.bulk.prefetch.tensor.3d.L2.global [%0, {%1, %2, %3}];\n}\n" ::"l"(tm), "r"(c0), "r"(c1), "r"(0) : "memory");
}
#define WAIT_EXPECT "{\n.reg .pred p, q;\n.reg .u32 n;\n" SPIN("mbarrier.try_wait.parity.shared::cta.b64 p, [%0], %1;\n") \
  "elect.sync _|p, 0xffffffff;\n@p mbarrier.arrive.expect_tx.shared::cta.b64 _, [%2], %3;\n"
template <int BYTES> DEV void w_load(u32 be, u32 par, u32 bf, u32 dst, const void* src) {
  asm volatile(WAIT_EXPECT "@p cp.async.bulk.shared::cluster.global.mbarrier::complete_tx::bytes [%4], [%5], %3, [%2];\n}\n"
               ::"r"(be), "r"(par), "r"(bf), "n"(BYTES), "r"(dst), "l"(src) : "memory");
}
DEV void w_g1(u32 be, u32 par, u32 bf, u32 dst, const void* tm, int c0, int c1, const void* src) {
  asm volatile(WAIT_EXPECT "@p cp.async.bulk.tensor.3d.shared::cluster.global.mbarrier::complete_tx::bytes [%4], [%5, {%6, %7, %8}], [%2];\n"
               "@p cp.async.bulk.shared::cluster.global.mbarrier::complete_tx::bytes [%9], [%10], 11264, [%2];\n}\n"
               ::"r"(be), "r"(par), "r"(bf), "n"(BT), "r"(dst), "l"(tm), "r"(c0), "r"(c1), "r"(0), "r"(dst + 16384), "l"(src) : "memory");
}
DEV void w_g2(u32 be, u32 par, u32 bf, u32 db, const void* src, u32 da, const void* tm, int c0, int c1) {
  asm volatile(WAIT_EXPECT "@p cp.async.bulk.shared::cluster.global.mbarrier::complete_tx::bytes [%4], [%5], %10, [%2];\n"
               "@p cp.async.bulk.tensor.2d.shared::cluster.global.mbarrier::complete_tx::bytes [%6], [%7, {%8, %9}], [%2];\n}\n"
               ::"r"(be), "r"(par), "r"(bf), "n"(BT + 8192), "r"(db), "l"(src), "r"(da), "l"(tm), "r"(c0), "r"(c1), "n"(BT) : "memory");
}
DEV void load1d(u32 dst, const void* src, u32 bytes, u32 bar) {
  asm volatile("cp.async.bulk.shared::cluster.global.mbarrier::complete_tx::bytes [%0], [%1], %2, [%3];" ::"r"(dst), "l"(src), "r"(bytes), "r"(bar) : "memory");
}
DEV void pf2d(const void* tm, int c0, int c1) { asm volatile("cp.async.bulk.prefetch.tensor.2d.L2.global [%0, {%1, %2}];" ::"l"(tm), "r"(c0), "r"(c1) : "memory"); }
DEV void xtma2d(u32 dst, const void* tm, u32 bar, int c0, int c1, u32 bytes) {
  asm volatile("mbarrier.arrive.expect_tx.shared::cta.b64 _, [%2], %5;\ncp.async.bulk.tensor.2d.shared::cluster.global.mbarrier::complete_tx::bytes [%0], [%1, {%3, %4}], [%2];"
               ::"r"(dst), "l"(tm), "r"(bar), "r"(c0), "r"(c1), "r"(bytes) : "memory");
}
DEV void xload(u32 dst, const void* src, u32 bytes, u32 bar) {
  asm volatile("mbarrier.arrive.expect_tx.shared::cta.b64 _, [%3], %2;\ncp.async.bulk.shared::cluster.global.mbarrier::complete_tx::bytes [%0], [%1], %2, [%3];"
               ::"r"(dst), "l"(src), "r"(bytes), "r"(bar) : "memory");
}
DEV void e_prefetch(const void* src, u32 bytes) { asm volatile(ELECT "@p cp.async.bulk.prefetch.L2.global [%0], %1;\n}\n" ::"l"(src), "r"(bytes) : "memory"); }
DEV void e_tmpf(const void* tm) { asm volatile(ELECT "@p prefetch.tensormap [%0];\n}\n" ::"l"(tm) : "memory"); }
DEV uint4 ld_nc(const void* p) { uint4 v; asm volatile("ld.global.nc.v4.u32 {%0,%1,%2,%3}, [%4];" : "=r"(v.x), "=r"(v.y), "=r"(v.z), "=r"(v.w) : "l"(p)); return v; }
DEV void ldg128(u32* v, const void* p) { asm volatile("ld.global.cg.v4.u32 {%0,%1,%2,%3}, [%4];" : "=r"(v[0]), "=r"(v[1]), "=r"(v[2]), "=r"(v[3]) : "l"(p) : "memory"); }
DEV uint4 ld_rlx128(const void* p) {
  u64 a, b; asm volatile("ld.relaxed.gpu.global.v2.b64 {%0,%1}, [%2];" : "=l"(a), "=l"(b) : "l"(p) : "memory");
  return make_uint4((u32)a, (u32)(a >> 32), (u32)b, (u32)(b >> 32));
}
DEV uint2 ld_rlx64(const void* p) { u64 a; asm volatile("ld.relaxed.gpu.global.b64 %0, [%1];" : "=l"(a) : "l"(p) : "memory"); return make_uint2((u32)a, (u32)(a >> 32)); }
DEV void cp16(u32 dst, const void* src) { asm volatile("cp.async.cg.shared.global [%0], [%1], 16;" ::"r"(dst), "l"(src) : "memory"); }
DEV void cp_wait() { asm volatile("cp.async.wait_all;" ::: "memory"); }
DEV void bulk_store(void* dst, u32 src, u32 bytes) {
  asm volatile("cp.async.bulk.global.shared::cta.bulk_group [%0], [%1], %2;\ncp.async.bulk.commit_group;" ::"l"(dst), "r"(src), "r"(bytes) : "memory");
}
DEV void bulk_wait() { asm volatile("cp.async.bulk.wait_group 0;" ::: "memory"); }
DEV u32 ld_rlx32(const void* p) { u32 a; asm volatile("ld.relaxed.gpu.global.u32 %0, [%1];" : "=r"(a) : "l"(p) : "memory"); return a; }
DEV void ctr_arrive(u32* ctr, int f, u32 ep, u32 sel) {
  asm volatile("{\n.reg .pred p;\nsetp.eq.u32 p, %2, 0;\n@p red.relaxed.gpu.global.add.u32 [%0], %1;\n}\n"
               ::"l"(ctr + 1 + sel), "r"((1u - 2u * (ep & 1)) << (8 * f)), "r"(sel) : "memory");
}
DEV void ctr_poll(u32* ctr, int f, u32 ep, u32 n) {
  const u32 want = (ep & 1) ? 0 : n;
  int it = 0;
#pragma unroll 1
  while (__any_sync(0xffffffffu, ((ld_rlx32(ctr + 1) >> (8 * f)) & 255) != want)) trap_if_gt(++it, 1 << 20);
}
DEV void stamp_post(u32* ctr, u32 ep, int i, u32 t0, u32 sel) {
  asm volatile("{\n.reg .pred p;\nsetp.eq.u32 p, %2, 0;\n@p red.relaxed.gpu.global.max.u32 [%0+4], %1;\n@p red.relaxed.gpu.global.add.u32 [%0], 1;\n}\n"
               ::"l"(ctr + 8 + 8 * (ep & 1) + 2 * i + sel), "r"((u32)clock() - t0), "r"(sel) : "memory");
}
DEV int stamp_wait(u32* ctr, u32 ep, int i) {
  uint2 v = make_uint2(0, 0);
  int it = 0;
#pragma unroll 1
  while (__any_sync(0xffffffffu, v.x != 128)) { v = ld_rlx64(ctr + 8 + 8 * (ep & 1) + 2 * i); trap_if_gt(++it, 1 << 20); }
  return v.y;
}
DEV void tile_post(u32* w, u32 t0, u32 ep, bool c) { if (c) asm volatile("st.relaxed.gpu.global.u32 [%0], %1;" ::"l"(w), "r"(min((u32)clock() - t0, 0xfffffu) ^ ((ep + 1) << 20)) : "memory"); }
DEV int tile_wait(const u32* w, u32 ep) {
  u32 m;
  int it = 0;
#pragma unroll 1
  do {
    const uint2 a = ld_rlx64(w), b = ld_rlx64(w + 2);
    const u32 e = (ep + 1) << 20;
    m = max(max(a.x ^ e, a.y ^ e), max(b.x ^ e, b.y ^ e));
    trap_if_gt(++it, 1 << 20);
  } while (__any_sync(0xffffffffu, m >> 20));
  return m;
}
DEV void stg128(void* p, uint4 v) { asm volatile("st.global.v4.b32 [%0], {%1,%2,%3,%4};" ::"l"(p), "r"(v.x), "r"(v.y), "r"(v.z), "r"(v.w) : "memory"); }
DEV void stg32(void* p, u32 v) { asm volatile("st.global.b32 [%0], %1;" ::"l"(p), "r"(v) : "memory"); }
DEV void stg32_if(void* p, u32 v, bool c) { asm volatile("{\n.reg .pred q;\nsetp.ne.u32 q, %2, 0;\n@q st.global.b32 [%0], %1;\n}\n" ::"l"(p), "r"(v), "r"((u32)c) : "memory"); }
DEV u32 lds32(u32 a) { u32 v; asm volatile("ld.shared.b32 %0, [%1];" : "=r"(v) : "r"(a) : "memory"); return v; }
DEV void lds64(u32* v, u32 a) { asm volatile("ld.shared.v2.b32 {%0,%1}, [%2];" : "=r"(v[0]), "=r"(v[1]) : "r"(a) : "memory"); }
DEV uint4 lds128(u32 a) { uint4 v; asm volatile("ld.shared.v4.b32 {%0,%1,%2,%3}, [%4];" : "=r"(v.x), "=r"(v.y), "=r"(v.z), "=r"(v.w) : "r"(a) : "memory"); return v; }
DEV void lds128(u32* v, u32 a) { asm volatile("ld.shared.v4.b32 {%0,%1,%2,%3}, [%4];" : "=r"(v[0]), "=r"(v[1]), "=r"(v[2]), "=r"(v[3]) : "r"(a) : "memory"); }
DEV void sts16(u32 a, u32 v) { asm volatile("st.shared.b16 [%0], %1;" ::"r"(a), "h"((u16)v) : "memory"); }
DEV void sts32(u32 a, u32 v) { asm volatile("st.shared.b32 [%0], %1;" ::"r"(a), "r"(v) : "memory"); }
DEV void sts64f(u32 a, float x, float y) { asm volatile("st.shared.v2.f32 [%0], {%1,%2};" ::"r"(a), "f"(x), "f"(y) : "memory"); }
DEV void sts128(u32 a, uint4 v) { asm volatile("st.shared.v4.b32 [%0], {%1,%2,%3,%4};" ::"r"(a), "r"(v.x), "r"(v.y), "r"(v.z), "r"(v.w) : "memory"); }
DEV void consume(u32 x) { asm volatile("{\n.reg .pred p;\nsetp.eq.u32 p, %0, 0x7fc12345;\n@p nanosleep.u32 0;\n}\n" ::"r"(x) : "memory"); }
DEV int lane_now() { int l; asm volatile("mov.u32 %0, %%laneid;" : "=r"(l)); return l; }
DEV u32 opaque(u32 x) { asm volatile("" : "+r"(x)); return x; }
DEV void ldsm4(u32* r, u32 a) { asm volatile("ldmatrix.sync.aligned.m8n8.x4.shared.b16 {%0,%1,%2,%3}, [%4];" : "=r"(r[0]), "=r"(r[1]), "=r"(r[2]), "=r"(r[3]) : "r"(a) : "memory"); }
DEV void ldsm4t(u32* r, u32 a) { asm volatile("ldmatrix.sync.aligned.m8n8.x4.trans.shared.b16 {%0,%1,%2,%3}, [%4];" : "=r"(r[0]), "=r"(r[1]), "=r"(r[2]), "=r"(r[3]) : "r"(a) : "memory"); }
DEV void stsm4(u32 a, const u32* r) { asm volatile("stmatrix.sync.aligned.m8n8.x4.shared.b16 [%0], {%1,%2,%3,%4};" ::"r"(a), "r"(r[0]), "r"(r[1]), "r"(r[2]), "r"(r[3]) : "memory"); }
DEV void stsm4t(u32 a, const u32* r) { asm volatile("stmatrix.sync.aligned.m8n8.x4.trans.shared.b16 [%0], {%1,%2,%3,%4};" ::"r"(a), "r"(r[0]), "r"(r[1]), "r"(r[2]), "r"(r[3]) : "memory"); }
DEV void stsm2(u32 a, u32 r0, u32 r1) { asm volatile("stmatrix.sync.aligned.m8n8.x2.shared.b16 [%0], {%1,%2};" ::"r"(a), "r"(r0), "r"(r1) : "memory"); }
DEV void mma16816(float* c, u32 a0, u32 a1, u32 a2, u32 a3, u32 b0, u32 b1) {
  asm volatile("mma.sync.aligned.m16n8k16.row.col.f32.bf16.bf16.f32 {%0,%1,%2,%3}, {%4,%5,%6,%7}, {%8,%9}, {%0,%1,%2,%3};"
      : "+f"(c[0]), "+f"(c[1]), "+f"(c[2]), "+f"(c[3]) : "r"(a0), "r"(a1), "r"(a2), "r"(a3), "r"(b0), "r"(b1));
}
constexpr u32 ONE2 = 0x3f803f80u;
DEV u32 prmt(u32 a, u32 b, u32 s) { u32 r; asm("prmt.b32 %0, %1, %2, %3;" : "=r"(r) : "r"(a), "r"(b), "r"(s)); return r; }
DEV u32 hmul2(u32 a, u32 b) { u32 r; asm("mul.rn.bf16x2 %0, %1, %2;" : "=r"(r) : "r"(a), "r"(b)); return r; }
DEV u32 hadd2(u32 a, u32 b) { u32 r; asm("add.rn.bf16x2 %0, %1, %2;" : "=r"(r) : "r"(a), "r"(b)); return r; }
DEV u32 hfma2(u32 a, u32 b, u32 c) { u32 r; asm("fma.rn.bf16x2 %0, %1, %2, %3;" : "=r"(r) : "r"(a), "r"(b), "r"(c)); return r; }
DEV void row_stats(float (*c)[4], const u32* x) {
  mma16816(c[0], x[0], x[1], x[2], x[3], ONE2, ONE2);
  mma16816(c[1], x[0], x[1], x[2], x[3], x[0], x[2]);
  mma16816(c[2], x[0], x[1], x[2], x[3], x[1], x[3]);
}
DEV u32 pack2(float lo, float hi) { u32 r; asm("cvt.rn.bf16x2.f32 %0, %1, %2;" : "=r"(r) : "f"(hi), "f"(lo)); return r; }
DEV float bflo(u32 w) { return __uint_as_float(w * 65536u); }
DEV float bfhi(u32 w) { return __uint_as_float(w & 0xffff0000u); }
DEV u32 tagw(u32 w, u32 m, u32 par) { return (w & ~m) | (par & m); }
DEV u32 nz(u32 w) { return max(w, 1u); }
DEV float rsq(float x) { float r; asm("rsqrt.approx.ftz.f32 %0, %1;" : "=f"(r) : "f"(x)); return r; }
DEV float tanh_fast(float x) { float r; asm("tanh.approx.f32 %0, %1;" : "=f"(r) : "f"(x)); return r; }
DEV float shx(float v, int m) { return __shfl_xor_sync(0xffffffffu, v, m); }
DEV void wgmma_ss_128(float* d, u64 da, u64 db, int sd) {
  asm volatile("{\n.reg .pred p;\nsetp.ne.b32 p, %66, 0;\nwgmma.mma_async.sync.aligned.m64n128k16.f32.bf16.bf16 {%0, %1, %2, %3, %4, %5, %6, %7, %8, %9, %10, %11, %12, %13, %14, %15, %16, %17, %18, %19, %20, %21, %22, %23, %24, %25, %26, %27, %28, %29, %30, %31, %32, %33, %34, %35, %36, %37, %38, %39, %40, %41, %42, %43, %44, %45, %46, %47, %48, %49, %50, %51, %52, %53, %54, %55, %56, %57, %58, %59, %60, %61, %62, %63}, %64, %65, p, 1, 1, 0, 1;\n}\n"
    : "+f"(d[0]), "+f"(d[1]), "+f"(d[2]), "+f"(d[3]), "+f"(d[4]), "+f"(d[5]), "+f"(d[6]), "+f"(d[7]), "+f"(d[8]), "+f"(d[9]), "+f"(d[10]), "+f"(d[11]), "+f"(d[12]), "+f"(d[13]), "+f"(d[14]), "+f"(d[15]), "+f"(d[16]), "+f"(d[17]), "+f"(d[18]), "+f"(d[19]), "+f"(d[20]), "+f"(d[21]), "+f"(d[22]), "+f"(d[23]), "+f"(d[24]), "+f"(d[25]), "+f"(d[26]), "+f"(d[27]), "+f"(d[28]), "+f"(d[29]), "+f"(d[30]), "+f"(d[31]), "+f"(d[32]), "+f"(d[33]), "+f"(d[34]), "+f"(d[35]), "+f"(d[36]), "+f"(d[37]), "+f"(d[38]), "+f"(d[39]), "+f"(d[40]), "+f"(d[41]), "+f"(d[42]), "+f"(d[43]), "+f"(d[44]), "+f"(d[45]), "+f"(d[46]), "+f"(d[47]), "+f"(d[48]), "+f"(d[49]), "+f"(d[50]), "+f"(d[51]), "+f"(d[52]), "+f"(d[53]), "+f"(d[54]), "+f"(d[55]), "+f"(d[56]), "+f"(d[57]), "+f"(d[58]), "+f"(d[59]), "+f"(d[60]), "+f"(d[61]), "+f"(d[62]), "+f"(d[63]) : "l"(da), "l"(db), "r"(sd));
}
DEV void wgmma_ss_88(float* d, u64 da, u64 db, int sd) {
  asm volatile("{\n.reg .pred p;\nsetp.ne.b32 p, %46, 0;\nwgmma.mma_async.sync.aligned.m64n88k16.f32.bf16.bf16 {%0, %1, %2, %3, %4, %5, %6, %7, %8, %9, %10, %11, %12, %13, %14, %15, %16, %17, %18, %19, %20, %21, %22, %23, %24, %25, %26, %27, %28, %29, %30, %31, %32, %33, %34, %35, %36, %37, %38, %39, %40, %41, %42, %43}, %44, %45, p, 1, 1, 0, 1;\n}\n"
    : "+f"(d[0]), "+f"(d[1]), "+f"(d[2]), "+f"(d[3]), "+f"(d[4]), "+f"(d[5]), "+f"(d[6]), "+f"(d[7]), "+f"(d[8]), "+f"(d[9]), "+f"(d[10]), "+f"(d[11]), "+f"(d[12]), "+f"(d[13]), "+f"(d[14]), "+f"(d[15]), "+f"(d[16]), "+f"(d[17]), "+f"(d[18]), "+f"(d[19]), "+f"(d[20]), "+f"(d[21]), "+f"(d[22]), "+f"(d[23]), "+f"(d[24]), "+f"(d[25]), "+f"(d[26]), "+f"(d[27]), "+f"(d[28]), "+f"(d[29]), "+f"(d[30]), "+f"(d[31]), "+f"(d[32]), "+f"(d[33]), "+f"(d[34]), "+f"(d[35]), "+f"(d[36]), "+f"(d[37]), "+f"(d[38]), "+f"(d[39]), "+f"(d[40]), "+f"(d[41]), "+f"(d[42]), "+f"(d[43]) : "l"(da), "l"(db), "r"(sd));
}
DEV void wgmma_ss_160(float* d, u64 da, u64 db, int sd) {
  asm volatile("{\n.reg .pred p;\nsetp.ne.b32 p, %82, 0;\nwgmma.mma_async.sync.aligned.m64n160k16.f32.bf16.bf16 {%0, %1, %2, %3, %4, %5, %6, %7, %8, %9, %10, %11, %12, %13, %14, %15, %16, %17, %18, %19, %20, %21, %22, %23, %24, %25, %26, %27, %28, %29, %30, %31, %32, %33, %34, %35, %36, %37, %38, %39, %40, %41, %42, %43, %44, %45, %46, %47, %48, %49, %50, %51, %52, %53, %54, %55, %56, %57, %58, %59, %60, %61, %62, %63, %64, %65, %66, %67, %68, %69, %70, %71, %72, %73, %74, %75, %76, %77, %78, %79}, %80, %81, p, 1, 1, 0, 1;\n}\n"
    : "+f"(d[0]), "+f"(d[1]), "+f"(d[2]), "+f"(d[3]), "+f"(d[4]), "+f"(d[5]), "+f"(d[6]), "+f"(d[7]), "+f"(d[8]), "+f"(d[9]), "+f"(d[10]), "+f"(d[11]), "+f"(d[12]), "+f"(d[13]), "+f"(d[14]), "+f"(d[15]), "+f"(d[16]), "+f"(d[17]), "+f"(d[18]), "+f"(d[19]), "+f"(d[20]), "+f"(d[21]), "+f"(d[22]), "+f"(d[23]), "+f"(d[24]), "+f"(d[25]), "+f"(d[26]), "+f"(d[27]), "+f"(d[28]), "+f"(d[29]), "+f"(d[30]), "+f"(d[31]), "+f"(d[32]), "+f"(d[33]), "+f"(d[34]), "+f"(d[35]), "+f"(d[36]), "+f"(d[37]), "+f"(d[38]), "+f"(d[39]), "+f"(d[40]), "+f"(d[41]), "+f"(d[42]), "+f"(d[43]), "+f"(d[44]), "+f"(d[45]), "+f"(d[46]), "+f"(d[47]), "+f"(d[48]), "+f"(d[49]), "+f"(d[50]), "+f"(d[51]), "+f"(d[52]), "+f"(d[53]), "+f"(d[54]), "+f"(d[55]), "+f"(d[56]), "+f"(d[57]), "+f"(d[58]), "+f"(d[59]), "+f"(d[60]), "+f"(d[61]), "+f"(d[62]), "+f"(d[63]), "+f"(d[64]), "+f"(d[65]), "+f"(d[66]), "+f"(d[67]), "+f"(d[68]), "+f"(d[69]), "+f"(d[70]), "+f"(d[71]), "+f"(d[72]), "+f"(d[73]), "+f"(d[74]), "+f"(d[75]), "+f"(d[76]), "+f"(d[77]), "+f"(d[78]), "+f"(d[79]) : "l"(da), "l"(db), "r"(sd));
}
template <int N> DEV void wgmma_rs(float* d, const u32* a, u64 db);
template <> DEV void wgmma_rs<256>(float* d, const u32* a, u64 db) {
  asm volatile("wgmma.mma_async.sync.aligned.m64n256k16.f32.bf16.bf16 {%0, %1, %2, %3, %4, %5, %6, %7, %8, %9, %10, %11, %12, %13, %14, %15, %16, %17, %18, %19, %20, %21, %22, %23, %24, %25, %26, %27, %28, %29, %30, %31, %32, %33, %34, %35, %36, %37, %38, %39, %40, %41, %42, %43, %44, %45, %46, %47, %48, %49, %50, %51, %52, %53, %54, %55, %56, %57, %58, %59, %60, %61, %62, %63, %64, %65, %66, %67, %68, %69, %70, %71, %72, %73, %74, %75, %76, %77, %78, %79, %80, %81, %82, %83, %84, %85, %86, %87, %88, %89, %90, %91, %92, %93, %94, %95, %96, %97, %98, %99, %100, %101, %102, %103, %104, %105, %106, %107, %108, %109, %110, %111, %112, %113, %114, %115, %116, %117, %118, %119, %120, %121, %122, %123, %124, %125, %126, %127}, {%128, %129, %130, %131}, %132, 0, 1, 1, 0;"
    : "+f"(d[0]), "+f"(d[1]), "+f"(d[2]), "+f"(d[3]), "+f"(d[4]), "+f"(d[5]), "+f"(d[6]), "+f"(d[7]), "+f"(d[8]), "+f"(d[9]), "+f"(d[10]), "+f"(d[11]), "+f"(d[12]), "+f"(d[13]), "+f"(d[14]), "+f"(d[15]), "+f"(d[16]), "+f"(d[17]), "+f"(d[18]), "+f"(d[19]), "+f"(d[20]), "+f"(d[21]), "+f"(d[22]), "+f"(d[23]), "+f"(d[24]), "+f"(d[25]), "+f"(d[26]), "+f"(d[27]), "+f"(d[28]), "+f"(d[29]), "+f"(d[30]), "+f"(d[31]), "+f"(d[32]), "+f"(d[33]), "+f"(d[34]), "+f"(d[35]), "+f"(d[36]), "+f"(d[37]), "+f"(d[38]), "+f"(d[39]), "+f"(d[40]), "+f"(d[41]), "+f"(d[42]), "+f"(d[43]), "+f"(d[44]), "+f"(d[45]), "+f"(d[46]), "+f"(d[47]), "+f"(d[48]), "+f"(d[49]), "+f"(d[50]), "+f"(d[51]), "+f"(d[52]), "+f"(d[53]), "+f"(d[54]), "+f"(d[55]), "+f"(d[56]), "+f"(d[57]), "+f"(d[58]), "+f"(d[59]), "+f"(d[60]), "+f"(d[61]), "+f"(d[62]), "+f"(d[63]), "+f"(d[64]), "+f"(d[65]), "+f"(d[66]), "+f"(d[67]), "+f"(d[68]), "+f"(d[69]), "+f"(d[70]), "+f"(d[71]), "+f"(d[72]), "+f"(d[73]), "+f"(d[74]), "+f"(d[75]), "+f"(d[76]), "+f"(d[77]), "+f"(d[78]), "+f"(d[79]), "+f"(d[80]), "+f"(d[81]), "+f"(d[82]), "+f"(d[83]), "+f"(d[84]), "+f"(d[85]), "+f"(d[86]), "+f"(d[87]), "+f"(d[88]), "+f"(d[89]), "+f"(d[90]), "+f"(d[91]), "+f"(d[92]), "+f"(d[93]), "+f"(d[94]), "+f"(d[95]), "+f"(d[96]), "+f"(d[97]), "+f"(d[98]), "+f"(d[99]), "+f"(d[100]), "+f"(d[101]), "+f"(d[102]), "+f"(d[103]), "+f"(d[104]), "+f"(d[105]), "+f"(d[106]), "+f"(d[107]), "+f"(d[108]), "+f"(d[109]), "+f"(d[110]), "+f"(d[111]), "+f"(d[112]), "+f"(d[113]), "+f"(d[114]), "+f"(d[115]), "+f"(d[116]), "+f"(d[117]), "+f"(d[118]), "+f"(d[119]), "+f"(d[120]), "+f"(d[121]), "+f"(d[122]), "+f"(d[123]), "+f"(d[124]), "+f"(d[125]), "+f"(d[126]), "+f"(d[127]) : "r"(a[0]), "r"(a[1]), "r"(a[2]), "r"(a[3]), "l"(db));
}
template <> DEV void wgmma_rs<240>(float* d, const u32* a, u64 db) {
  asm volatile("wgmma.mma_async.sync.aligned.m64n240k16.f32.bf16.bf16 {%0, %1, %2, %3, %4, %5, %6, %7, %8, %9, %10, %11, %12, %13, %14, %15, %16, %17, %18, %19, %20, %21, %22, %23, %24, %25, %26, %27, %28, %29, %30, %31, %32, %33, %34, %35, %36, %37, %38, %39, %40, %41, %42, %43, %44, %45, %46, %47, %48, %49, %50, %51, %52, %53, %54, %55, %56, %57, %58, %59, %60, %61, %62, %63, %64, %65, %66, %67, %68, %69, %70, %71, %72, %73, %74, %75, %76, %77, %78, %79, %80, %81, %82, %83, %84, %85, %86, %87, %88, %89, %90, %91, %92, %93, %94, %95, %96, %97, %98, %99, %100, %101, %102, %103, %104, %105, %106, %107, %108, %109, %110, %111, %112, %113, %114, %115, %116, %117, %118, %119}, {%120, %121, %122, %123}, %124, 1, 1, 1, 0;"
    : "+f"(d[0]), "+f"(d[1]), "+f"(d[2]), "+f"(d[3]), "+f"(d[4]), "+f"(d[5]), "+f"(d[6]), "+f"(d[7]), "+f"(d[8]), "+f"(d[9]), "+f"(d[10]), "+f"(d[11]), "+f"(d[12]), "+f"(d[13]), "+f"(d[14]), "+f"(d[15]), "+f"(d[16]), "+f"(d[17]), "+f"(d[18]), "+f"(d[19]), "+f"(d[20]), "+f"(d[21]), "+f"(d[22]), "+f"(d[23]), "+f"(d[24]), "+f"(d[25]), "+f"(d[26]), "+f"(d[27]), "+f"(d[28]), "+f"(d[29]), "+f"(d[30]), "+f"(d[31]), "+f"(d[32]), "+f"(d[33]), "+f"(d[34]), "+f"(d[35]), "+f"(d[36]), "+f"(d[37]), "+f"(d[38]), "+f"(d[39]), "+f"(d[40]), "+f"(d[41]), "+f"(d[42]), "+f"(d[43]), "+f"(d[44]), "+f"(d[45]), "+f"(d[46]), "+f"(d[47]), "+f"(d[48]), "+f"(d[49]), "+f"(d[50]), "+f"(d[51]), "+f"(d[52]), "+f"(d[53]), "+f"(d[54]), "+f"(d[55]), "+f"(d[56]), "+f"(d[57]), "+f"(d[58]), "+f"(d[59]), "+f"(d[60]), "+f"(d[61]), "+f"(d[62]), "+f"(d[63]), "+f"(d[64]), "+f"(d[65]), "+f"(d[66]), "+f"(d[67]), "+f"(d[68]), "+f"(d[69]), "+f"(d[70]), "+f"(d[71]), "+f"(d[72]), "+f"(d[73]), "+f"(d[74]), "+f"(d[75]), "+f"(d[76]), "+f"(d[77]), "+f"(d[78]), "+f"(d[79]), "+f"(d[80]), "+f"(d[81]), "+f"(d[82]), "+f"(d[83]), "+f"(d[84]), "+f"(d[85]), "+f"(d[86]), "+f"(d[87]), "+f"(d[88]), "+f"(d[89]), "+f"(d[90]), "+f"(d[91]), "+f"(d[92]), "+f"(d[93]), "+f"(d[94]), "+f"(d[95]), "+f"(d[96]), "+f"(d[97]), "+f"(d[98]), "+f"(d[99]), "+f"(d[100]), "+f"(d[101]), "+f"(d[102]), "+f"(d[103]), "+f"(d[104]), "+f"(d[105]), "+f"(d[106]), "+f"(d[107]), "+f"(d[108]), "+f"(d[109]), "+f"(d[110]), "+f"(d[111]), "+f"(d[112]), "+f"(d[113]), "+f"(d[114]), "+f"(d[115]), "+f"(d[116]), "+f"(d[117]), "+f"(d[118]), "+f"(d[119]) : "r"(a[0]), "r"(a[1]), "r"(a[2]), "r"(a[3]), "l"(db));
}
template <> DEV void wgmma_rs<224>(float* d, const u32* a, u64 db) {
  asm volatile("wgmma.mma_async.sync.aligned.m64n224k16.f32.bf16.bf16 {%0, %1, %2, %3, %4, %5, %6, %7, %8, %9, %10, %11, %12, %13, %14, %15, %16, %17, %18, %19, %20, %21, %22, %23, %24, %25, %26, %27, %28, %29, %30, %31, %32, %33, %34, %35, %36, %37, %38, %39, %40, %41, %42, %43, %44, %45, %46, %47, %48, %49, %50, %51, %52, %53, %54, %55, %56, %57, %58, %59, %60, %61, %62, %63, %64, %65, %66, %67, %68, %69, %70, %71, %72, %73, %74, %75, %76, %77, %78, %79, %80, %81, %82, %83, %84, %85, %86, %87, %88, %89, %90, %91, %92, %93, %94, %95, %96, %97, %98, %99, %100, %101, %102, %103, %104, %105, %106, %107, %108, %109, %110, %111}, {%112, %113, %114, %115}, %116, 1, 1, 1, 0;"
    : "+f"(d[0]), "+f"(d[1]), "+f"(d[2]), "+f"(d[3]), "+f"(d[4]), "+f"(d[5]), "+f"(d[6]), "+f"(d[7]), "+f"(d[8]), "+f"(d[9]), "+f"(d[10]), "+f"(d[11]), "+f"(d[12]), "+f"(d[13]), "+f"(d[14]), "+f"(d[15]), "+f"(d[16]), "+f"(d[17]), "+f"(d[18]), "+f"(d[19]), "+f"(d[20]), "+f"(d[21]), "+f"(d[22]), "+f"(d[23]), "+f"(d[24]), "+f"(d[25]), "+f"(d[26]), "+f"(d[27]), "+f"(d[28]), "+f"(d[29]), "+f"(d[30]), "+f"(d[31]), "+f"(d[32]), "+f"(d[33]), "+f"(d[34]), "+f"(d[35]), "+f"(d[36]), "+f"(d[37]), "+f"(d[38]), "+f"(d[39]), "+f"(d[40]), "+f"(d[41]), "+f"(d[42]), "+f"(d[43]), "+f"(d[44]), "+f"(d[45]), "+f"(d[46]), "+f"(d[47]), "+f"(d[48]), "+f"(d[49]), "+f"(d[50]), "+f"(d[51]), "+f"(d[52]), "+f"(d[53]), "+f"(d[54]), "+f"(d[55]), "+f"(d[56]), "+f"(d[57]), "+f"(d[58]), "+f"(d[59]), "+f"(d[60]), "+f"(d[61]), "+f"(d[62]), "+f"(d[63]), "+f"(d[64]), "+f"(d[65]), "+f"(d[66]), "+f"(d[67]), "+f"(d[68]), "+f"(d[69]), "+f"(d[70]), "+f"(d[71]), "+f"(d[72]), "+f"(d[73]), "+f"(d[74]), "+f"(d[75]), "+f"(d[76]), "+f"(d[77]), "+f"(d[78]), "+f"(d[79]), "+f"(d[80]), "+f"(d[81]), "+f"(d[82]), "+f"(d[83]), "+f"(d[84]), "+f"(d[85]), "+f"(d[86]), "+f"(d[87]), "+f"(d[88]), "+f"(d[89]), "+f"(d[90]), "+f"(d[91]), "+f"(d[92]), "+f"(d[93]), "+f"(d[94]), "+f"(d[95]), "+f"(d[96]), "+f"(d[97]), "+f"(d[98]), "+f"(d[99]), "+f"(d[100]), "+f"(d[101]), "+f"(d[102]), "+f"(d[103]), "+f"(d[104]), "+f"(d[105]), "+f"(d[106]), "+f"(d[107]), "+f"(d[108]), "+f"(d[109]), "+f"(d[110]), "+f"(d[111]) : "r"(a[0]), "r"(a[1]), "r"(a[2]), "r"(a[3]), "l"(db));
}
template <> DEV void wgmma_rs<208>(float* d, const u32* a, u64 db) {
  asm volatile("wgmma.mma_async.sync.aligned.m64n208k16.f32.bf16.bf16 {%0, %1, %2, %3, %4, %5, %6, %7, %8, %9, %10, %11, %12, %13, %14, %15, %16, %17, %18, %19, %20, %21, %22, %23, %24, %25, %26, %27, %28, %29, %30, %31, %32, %33, %34, %35, %36, %37, %38, %39, %40, %41, %42, %43, %44, %45, %46, %47, %48, %49, %50, %51, %52, %53, %54, %55, %56, %57, %58, %59, %60, %61, %62, %63, %64, %65, %66, %67, %68, %69, %70, %71, %72, %73, %74, %75, %76, %77, %78, %79, %80, %81, %82, %83, %84, %85, %86, %87, %88, %89, %90, %91, %92, %93, %94, %95, %96, %97, %98, %99, %100, %101, %102, %103}, {%104, %105, %106, %107}, %108, 1, 1, 1, 0;"
    : "+f"(d[0]), "+f"(d[1]), "+f"(d[2]), "+f"(d[3]), "+f"(d[4]), "+f"(d[5]), "+f"(d[6]), "+f"(d[7]), "+f"(d[8]), "+f"(d[9]), "+f"(d[10]), "+f"(d[11]), "+f"(d[12]), "+f"(d[13]), "+f"(d[14]), "+f"(d[15]), "+f"(d[16]), "+f"(d[17]), "+f"(d[18]), "+f"(d[19]), "+f"(d[20]), "+f"(d[21]), "+f"(d[22]), "+f"(d[23]), "+f"(d[24]), "+f"(d[25]), "+f"(d[26]), "+f"(d[27]), "+f"(d[28]), "+f"(d[29]), "+f"(d[30]), "+f"(d[31]), "+f"(d[32]), "+f"(d[33]), "+f"(d[34]), "+f"(d[35]), "+f"(d[36]), "+f"(d[37]), "+f"(d[38]), "+f"(d[39]), "+f"(d[40]), "+f"(d[41]), "+f"(d[42]), "+f"(d[43]), "+f"(d[44]), "+f"(d[45]), "+f"(d[46]), "+f"(d[47]), "+f"(d[48]), "+f"(d[49]), "+f"(d[50]), "+f"(d[51]), "+f"(d[52]), "+f"(d[53]), "+f"(d[54]), "+f"(d[55]), "+f"(d[56]), "+f"(d[57]), "+f"(d[58]), "+f"(d[59]), "+f"(d[60]), "+f"(d[61]), "+f"(d[62]), "+f"(d[63]), "+f"(d[64]), "+f"(d[65]), "+f"(d[66]), "+f"(d[67]), "+f"(d[68]), "+f"(d[69]), "+f"(d[70]), "+f"(d[71]), "+f"(d[72]), "+f"(d[73]), "+f"(d[74]), "+f"(d[75]), "+f"(d[76]), "+f"(d[77]), "+f"(d[78]), "+f"(d[79]), "+f"(d[80]), "+f"(d[81]), "+f"(d[82]), "+f"(d[83]), "+f"(d[84]), "+f"(d[85]), "+f"(d[86]), "+f"(d[87]), "+f"(d[88]), "+f"(d[89]), "+f"(d[90]), "+f"(d[91]), "+f"(d[92]), "+f"(d[93]), "+f"(d[94]), "+f"(d[95]), "+f"(d[96]), "+f"(d[97]), "+f"(d[98]), "+f"(d[99]), "+f"(d[100]), "+f"(d[101]), "+f"(d[102]), "+f"(d[103]) : "r"(a[0]), "r"(a[1]), "r"(a[2]), "r"(a[3]), "l"(db));
}
template <> DEV void wgmma_rs<192>(float* d, const u32* a, u64 db) {
  asm volatile("wgmma.mma_async.sync.aligned.m64n192k16.f32.bf16.bf16 {%0, %1, %2, %3, %4, %5, %6, %7, %8, %9, %10, %11, %12, %13, %14, %15, %16, %17, %18, %19, %20, %21, %22, %23, %24, %25, %26, %27, %28, %29, %30, %31, %32, %33, %34, %35, %36, %37, %38, %39, %40, %41, %42, %43, %44, %45, %46, %47, %48, %49, %50, %51, %52, %53, %54, %55, %56, %57, %58, %59, %60, %61, %62, %63, %64, %65, %66, %67, %68, %69, %70, %71, %72, %73, %74, %75, %76, %77, %78, %79, %80, %81, %82, %83, %84, %85, %86, %87, %88, %89, %90, %91, %92, %93, %94, %95}, {%96, %97, %98, %99}, %100, 1, 1, 1, 0;"
    : "+f"(d[0]), "+f"(d[1]), "+f"(d[2]), "+f"(d[3]), "+f"(d[4]), "+f"(d[5]), "+f"(d[6]), "+f"(d[7]), "+f"(d[8]), "+f"(d[9]), "+f"(d[10]), "+f"(d[11]), "+f"(d[12]), "+f"(d[13]), "+f"(d[14]), "+f"(d[15]), "+f"(d[16]), "+f"(d[17]), "+f"(d[18]), "+f"(d[19]), "+f"(d[20]), "+f"(d[21]), "+f"(d[22]), "+f"(d[23]), "+f"(d[24]), "+f"(d[25]), "+f"(d[26]), "+f"(d[27]), "+f"(d[28]), "+f"(d[29]), "+f"(d[30]), "+f"(d[31]), "+f"(d[32]), "+f"(d[33]), "+f"(d[34]), "+f"(d[35]), "+f"(d[36]), "+f"(d[37]), "+f"(d[38]), "+f"(d[39]), "+f"(d[40]), "+f"(d[41]), "+f"(d[42]), "+f"(d[43]), "+f"(d[44]), "+f"(d[45]), "+f"(d[46]), "+f"(d[47]), "+f"(d[48]), "+f"(d[49]), "+f"(d[50]), "+f"(d[51]), "+f"(d[52]), "+f"(d[53]), "+f"(d[54]), "+f"(d[55]), "+f"(d[56]), "+f"(d[57]), "+f"(d[58]), "+f"(d[59]), "+f"(d[60]), "+f"(d[61]), "+f"(d[62]), "+f"(d[63]), "+f"(d[64]), "+f"(d[65]), "+f"(d[66]), "+f"(d[67]), "+f"(d[68]), "+f"(d[69]), "+f"(d[70]), "+f"(d[71]), "+f"(d[72]), "+f"(d[73]), "+f"(d[74]), "+f"(d[75]), "+f"(d[76]), "+f"(d[77]), "+f"(d[78]), "+f"(d[79]), "+f"(d[80]), "+f"(d[81]), "+f"(d[82]), "+f"(d[83]), "+f"(d[84]), "+f"(d[85]), "+f"(d[86]), "+f"(d[87]), "+f"(d[88]), "+f"(d[89]), "+f"(d[90]), "+f"(d[91]), "+f"(d[92]), "+f"(d[93]), "+f"(d[94]), "+f"(d[95]) : "r"(a[0]), "r"(a[1]), "r"(a[2]), "r"(a[3]), "l"(db));
}
template <> DEV void wgmma_rs<176>(float* d, const u32* a, u64 db) {
  asm volatile("wgmma.mma_async.sync.aligned.m64n176k16.f32.bf16.bf16 {%0, %1, %2, %3, %4, %5, %6, %7, %8, %9, %10, %11, %12, %13, %14, %15, %16, %17, %18, %19, %20, %21, %22, %23, %24, %25, %26, %27, %28, %29, %30, %31, %32, %33, %34, %35, %36, %37, %38, %39, %40, %41, %42, %43, %44, %45, %46, %47, %48, %49, %50, %51, %52, %53, %54, %55, %56, %57, %58, %59, %60, %61, %62, %63, %64, %65, %66, %67, %68, %69, %70, %71, %72, %73, %74, %75, %76, %77, %78, %79, %80, %81, %82, %83, %84, %85, %86, %87}, {%88, %89, %90, %91}, %92, 1, 1, 1, 0;"
    : "+f"(d[0]), "+f"(d[1]), "+f"(d[2]), "+f"(d[3]), "+f"(d[4]), "+f"(d[5]), "+f"(d[6]), "+f"(d[7]), "+f"(d[8]), "+f"(d[9]), "+f"(d[10]), "+f"(d[11]), "+f"(d[12]), "+f"(d[13]), "+f"(d[14]), "+f"(d[15]), "+f"(d[16]), "+f"(d[17]), "+f"(d[18]), "+f"(d[19]), "+f"(d[20]), "+f"(d[21]), "+f"(d[22]), "+f"(d[23]), "+f"(d[24]), "+f"(d[25]), "+f"(d[26]), "+f"(d[27]), "+f"(d[28]), "+f"(d[29]), "+f"(d[30]), "+f"(d[31]), "+f"(d[32]), "+f"(d[33]), "+f"(d[34]), "+f"(d[35]), "+f"(d[36]), "+f"(d[37]), "+f"(d[38]), "+f"(d[39]), "+f"(d[40]), "+f"(d[41]), "+f"(d[42]), "+f"(d[43]), "+f"(d[44]), "+f"(d[45]), "+f"(d[46]), "+f"(d[47]), "+f"(d[48]), "+f"(d[49]), "+f"(d[50]), "+f"(d[51]), "+f"(d[52]), "+f"(d[53]), "+f"(d[54]), "+f"(d[55]), "+f"(d[56]), "+f"(d[57]), "+f"(d[58]), "+f"(d[59]), "+f"(d[60]), "+f"(d[61]), "+f"(d[62]), "+f"(d[63]), "+f"(d[64]), "+f"(d[65]), "+f"(d[66]), "+f"(d[67]), "+f"(d[68]), "+f"(d[69]), "+f"(d[70]), "+f"(d[71]), "+f"(d[72]), "+f"(d[73]), "+f"(d[74]), "+f"(d[75]), "+f"(d[76]), "+f"(d[77]), "+f"(d[78]), "+f"(d[79]), "+f"(d[80]), "+f"(d[81]), "+f"(d[82]), "+f"(d[83]), "+f"(d[84]), "+f"(d[85]), "+f"(d[86]), "+f"(d[87]) : "r"(a[0]), "r"(a[1]), "r"(a[2]), "r"(a[3]), "l"(db));
}
template <> DEV void wgmma_rs<160>(float* d, const u32* a, u64 db) {
  asm volatile("wgmma.mma_async.sync.aligned.m64n160k16.f32.bf16.bf16 {%0, %1, %2, %3, %4, %5, %6, %7, %8, %9, %10, %11, %12, %13, %14, %15, %16, %17, %18, %19, %20, %21, %22, %23, %24, %25, %26, %27, %28, %29, %30, %31, %32, %33, %34, %35, %36, %37, %38, %39, %40, %41, %42, %43, %44, %45, %46, %47, %48, %49, %50, %51, %52, %53, %54, %55, %56, %57, %58, %59, %60, %61, %62, %63, %64, %65, %66, %67, %68, %69, %70, %71, %72, %73, %74, %75, %76, %77, %78, %79}, {%80, %81, %82, %83}, %84, 1, 1, 1, 0;"
    : "+f"(d[0]), "+f"(d[1]), "+f"(d[2]), "+f"(d[3]), "+f"(d[4]), "+f"(d[5]), "+f"(d[6]), "+f"(d[7]), "+f"(d[8]), "+f"(d[9]), "+f"(d[10]), "+f"(d[11]), "+f"(d[12]), "+f"(d[13]), "+f"(d[14]), "+f"(d[15]), "+f"(d[16]), "+f"(d[17]), "+f"(d[18]), "+f"(d[19]), "+f"(d[20]), "+f"(d[21]), "+f"(d[22]), "+f"(d[23]), "+f"(d[24]), "+f"(d[25]), "+f"(d[26]), "+f"(d[27]), "+f"(d[28]), "+f"(d[29]), "+f"(d[30]), "+f"(d[31]), "+f"(d[32]), "+f"(d[33]), "+f"(d[34]), "+f"(d[35]), "+f"(d[36]), "+f"(d[37]), "+f"(d[38]), "+f"(d[39]), "+f"(d[40]), "+f"(d[41]), "+f"(d[42]), "+f"(d[43]), "+f"(d[44]), "+f"(d[45]), "+f"(d[46]), "+f"(d[47]), "+f"(d[48]), "+f"(d[49]), "+f"(d[50]), "+f"(d[51]), "+f"(d[52]), "+f"(d[53]), "+f"(d[54]), "+f"(d[55]), "+f"(d[56]), "+f"(d[57]), "+f"(d[58]), "+f"(d[59]), "+f"(d[60]), "+f"(d[61]), "+f"(d[62]), "+f"(d[63]), "+f"(d[64]), "+f"(d[65]), "+f"(d[66]), "+f"(d[67]), "+f"(d[68]), "+f"(d[69]), "+f"(d[70]), "+f"(d[71]), "+f"(d[72]), "+f"(d[73]), "+f"(d[74]), "+f"(d[75]), "+f"(d[76]), "+f"(d[77]), "+f"(d[78]), "+f"(d[79]) : "r"(a[0]), "r"(a[1]), "r"(a[2]), "r"(a[3]), "l"(db));
}
template <> DEV void wgmma_rs<144>(float* d, const u32* a, u64 db) {
  asm volatile("wgmma.mma_async.sync.aligned.m64n144k16.f32.bf16.bf16 {%0, %1, %2, %3, %4, %5, %6, %7, %8, %9, %10, %11, %12, %13, %14, %15, %16, %17, %18, %19, %20, %21, %22, %23, %24, %25, %26, %27, %28, %29, %30, %31, %32, %33, %34, %35, %36, %37, %38, %39, %40, %41, %42, %43, %44, %45, %46, %47, %48, %49, %50, %51, %52, %53, %54, %55, %56, %57, %58, %59, %60, %61, %62, %63, %64, %65, %66, %67, %68, %69, %70, %71}, {%72, %73, %74, %75}, %76, 1, 1, 1, 0;"
    : "+f"(d[0]), "+f"(d[1]), "+f"(d[2]), "+f"(d[3]), "+f"(d[4]), "+f"(d[5]), "+f"(d[6]), "+f"(d[7]), "+f"(d[8]), "+f"(d[9]), "+f"(d[10]), "+f"(d[11]), "+f"(d[12]), "+f"(d[13]), "+f"(d[14]), "+f"(d[15]), "+f"(d[16]), "+f"(d[17]), "+f"(d[18]), "+f"(d[19]), "+f"(d[20]), "+f"(d[21]), "+f"(d[22]), "+f"(d[23]), "+f"(d[24]), "+f"(d[25]), "+f"(d[26]), "+f"(d[27]), "+f"(d[28]), "+f"(d[29]), "+f"(d[30]), "+f"(d[31]), "+f"(d[32]), "+f"(d[33]), "+f"(d[34]), "+f"(d[35]), "+f"(d[36]), "+f"(d[37]), "+f"(d[38]), "+f"(d[39]), "+f"(d[40]), "+f"(d[41]), "+f"(d[42]), "+f"(d[43]), "+f"(d[44]), "+f"(d[45]), "+f"(d[46]), "+f"(d[47]), "+f"(d[48]), "+f"(d[49]), "+f"(d[50]), "+f"(d[51]), "+f"(d[52]), "+f"(d[53]), "+f"(d[54]), "+f"(d[55]), "+f"(d[56]), "+f"(d[57]), "+f"(d[58]), "+f"(d[59]), "+f"(d[60]), "+f"(d[61]), "+f"(d[62]), "+f"(d[63]), "+f"(d[64]), "+f"(d[65]), "+f"(d[66]), "+f"(d[67]), "+f"(d[68]), "+f"(d[69]), "+f"(d[70]), "+f"(d[71]) : "r"(a[0]), "r"(a[1]), "r"(a[2]), "r"(a[3]), "l"(db));
}
template <> DEV void wgmma_rs<128>(float* d, const u32* a, u64 db) {
  asm volatile("wgmma.mma_async.sync.aligned.m64n128k16.f32.bf16.bf16 {%0, %1, %2, %3, %4, %5, %6, %7, %8, %9, %10, %11, %12, %13, %14, %15, %16, %17, %18, %19, %20, %21, %22, %23, %24, %25, %26, %27, %28, %29, %30, %31, %32, %33, %34, %35, %36, %37, %38, %39, %40, %41, %42, %43, %44, %45, %46, %47, %48, %49, %50, %51, %52, %53, %54, %55, %56, %57, %58, %59, %60, %61, %62, %63}, {%64, %65, %66, %67}, %68, 1, 1, 1, 0;"
    : "+f"(d[0]), "+f"(d[1]), "+f"(d[2]), "+f"(d[3]), "+f"(d[4]), "+f"(d[5]), "+f"(d[6]), "+f"(d[7]), "+f"(d[8]), "+f"(d[9]), "+f"(d[10]), "+f"(d[11]), "+f"(d[12]), "+f"(d[13]), "+f"(d[14]), "+f"(d[15]), "+f"(d[16]), "+f"(d[17]), "+f"(d[18]), "+f"(d[19]), "+f"(d[20]), "+f"(d[21]), "+f"(d[22]), "+f"(d[23]), "+f"(d[24]), "+f"(d[25]), "+f"(d[26]), "+f"(d[27]), "+f"(d[28]), "+f"(d[29]), "+f"(d[30]), "+f"(d[31]), "+f"(d[32]), "+f"(d[33]), "+f"(d[34]), "+f"(d[35]), "+f"(d[36]), "+f"(d[37]), "+f"(d[38]), "+f"(d[39]), "+f"(d[40]), "+f"(d[41]), "+f"(d[42]), "+f"(d[43]), "+f"(d[44]), "+f"(d[45]), "+f"(d[46]), "+f"(d[47]), "+f"(d[48]), "+f"(d[49]), "+f"(d[50]), "+f"(d[51]), "+f"(d[52]), "+f"(d[53]), "+f"(d[54]), "+f"(d[55]), "+f"(d[56]), "+f"(d[57]), "+f"(d[58]), "+f"(d[59]), "+f"(d[60]), "+f"(d[61]), "+f"(d[62]), "+f"(d[63]) : "r"(a[0]), "r"(a[1]), "r"(a[2]), "r"(a[3]), "l"(db));
}
template <> DEV void wgmma_rs<112>(float* d, const u32* a, u64 db) {
  asm volatile("wgmma.mma_async.sync.aligned.m64n112k16.f32.bf16.bf16 {%0, %1, %2, %3, %4, %5, %6, %7, %8, %9, %10, %11, %12, %13, %14, %15, %16, %17, %18, %19, %20, %21, %22, %23, %24, %25, %26, %27, %28, %29, %30, %31, %32, %33, %34, %35, %36, %37, %38, %39, %40, %41, %42, %43, %44, %45, %46, %47, %48, %49, %50, %51, %52, %53, %54, %55}, {%56, %57, %58, %59}, %60, 1, 1, 1, 0;"
    : "+f"(d[0]), "+f"(d[1]), "+f"(d[2]), "+f"(d[3]), "+f"(d[4]), "+f"(d[5]), "+f"(d[6]), "+f"(d[7]), "+f"(d[8]), "+f"(d[9]), "+f"(d[10]), "+f"(d[11]), "+f"(d[12]), "+f"(d[13]), "+f"(d[14]), "+f"(d[15]), "+f"(d[16]), "+f"(d[17]), "+f"(d[18]), "+f"(d[19]), "+f"(d[20]), "+f"(d[21]), "+f"(d[22]), "+f"(d[23]), "+f"(d[24]), "+f"(d[25]), "+f"(d[26]), "+f"(d[27]), "+f"(d[28]), "+f"(d[29]), "+f"(d[30]), "+f"(d[31]), "+f"(d[32]), "+f"(d[33]), "+f"(d[34]), "+f"(d[35]), "+f"(d[36]), "+f"(d[37]), "+f"(d[38]), "+f"(d[39]), "+f"(d[40]), "+f"(d[41]), "+f"(d[42]), "+f"(d[43]), "+f"(d[44]), "+f"(d[45]), "+f"(d[46]), "+f"(d[47]), "+f"(d[48]), "+f"(d[49]), "+f"(d[50]), "+f"(d[51]), "+f"(d[52]), "+f"(d[53]), "+f"(d[54]), "+f"(d[55]) : "r"(a[0]), "r"(a[1]), "r"(a[2]), "r"(a[3]), "l"(db));
}
template <> DEV void wgmma_rs<96>(float* d, const u32* a, u64 db) {
  asm volatile("wgmma.mma_async.sync.aligned.m64n96k16.f32.bf16.bf16 {%0, %1, %2, %3, %4, %5, %6, %7, %8, %9, %10, %11, %12, %13, %14, %15, %16, %17, %18, %19, %20, %21, %22, %23, %24, %25, %26, %27, %28, %29, %30, %31, %32, %33, %34, %35, %36, %37, %38, %39, %40, %41, %42, %43, %44, %45, %46, %47}, {%48, %49, %50, %51}, %52, 1, 1, 1, 0;"
    : "+f"(d[0]), "+f"(d[1]), "+f"(d[2]), "+f"(d[3]), "+f"(d[4]), "+f"(d[5]), "+f"(d[6]), "+f"(d[7]), "+f"(d[8]), "+f"(d[9]), "+f"(d[10]), "+f"(d[11]), "+f"(d[12]), "+f"(d[13]), "+f"(d[14]), "+f"(d[15]), "+f"(d[16]), "+f"(d[17]), "+f"(d[18]), "+f"(d[19]), "+f"(d[20]), "+f"(d[21]), "+f"(d[22]), "+f"(d[23]), "+f"(d[24]), "+f"(d[25]), "+f"(d[26]), "+f"(d[27]), "+f"(d[28]), "+f"(d[29]), "+f"(d[30]), "+f"(d[31]), "+f"(d[32]), "+f"(d[33]), "+f"(d[34]), "+f"(d[35]), "+f"(d[36]), "+f"(d[37]), "+f"(d[38]), "+f"(d[39]), "+f"(d[40]), "+f"(d[41]), "+f"(d[42]), "+f"(d[43]), "+f"(d[44]), "+f"(d[45]), "+f"(d[46]), "+f"(d[47]) : "r"(a[0]), "r"(a[1]), "r"(a[2]), "r"(a[3]), "l"(db));
}
template <> DEV void wgmma_rs<80>(float* d, const u32* a, u64 db) {
  asm volatile("wgmma.mma_async.sync.aligned.m64n80k16.f32.bf16.bf16 {%0, %1, %2, %3, %4, %5, %6, %7, %8, %9, %10, %11, %12, %13, %14, %15, %16, %17, %18, %19, %20, %21, %22, %23, %24, %25, %26, %27, %28, %29, %30, %31, %32, %33, %34, %35, %36, %37, %38, %39}, {%40, %41, %42, %43}, %44, 1, 1, 1, 0;"
    : "+f"(d[0]), "+f"(d[1]), "+f"(d[2]), "+f"(d[3]), "+f"(d[4]), "+f"(d[5]), "+f"(d[6]), "+f"(d[7]), "+f"(d[8]), "+f"(d[9]), "+f"(d[10]), "+f"(d[11]), "+f"(d[12]), "+f"(d[13]), "+f"(d[14]), "+f"(d[15]), "+f"(d[16]), "+f"(d[17]), "+f"(d[18]), "+f"(d[19]), "+f"(d[20]), "+f"(d[21]), "+f"(d[22]), "+f"(d[23]), "+f"(d[24]), "+f"(d[25]), "+f"(d[26]), "+f"(d[27]), "+f"(d[28]), "+f"(d[29]), "+f"(d[30]), "+f"(d[31]), "+f"(d[32]), "+f"(d[33]), "+f"(d[34]), "+f"(d[35]), "+f"(d[36]), "+f"(d[37]), "+f"(d[38]), "+f"(d[39]) : "r"(a[0]), "r"(a[1]), "r"(a[2]), "r"(a[3]), "l"(db));
}
template <> DEV void wgmma_rs<64>(float* d, const u32* a, u64 db) {
  asm volatile("wgmma.mma_async.sync.aligned.m64n64k16.f32.bf16.bf16 {%0, %1, %2, %3, %4, %5, %6, %7, %8, %9, %10, %11, %12, %13, %14, %15, %16, %17, %18, %19, %20, %21, %22, %23, %24, %25, %26, %27, %28, %29, %30, %31}, {%32, %33, %34, %35}, %36, 1, 1, 1, 0;"
    : "+f"(d[0]), "+f"(d[1]), "+f"(d[2]), "+f"(d[3]), "+f"(d[4]), "+f"(d[5]), "+f"(d[6]), "+f"(d[7]), "+f"(d[8]), "+f"(d[9]), "+f"(d[10]), "+f"(d[11]), "+f"(d[12]), "+f"(d[13]), "+f"(d[14]), "+f"(d[15]), "+f"(d[16]), "+f"(d[17]), "+f"(d[18]), "+f"(d[19]), "+f"(d[20]), "+f"(d[21]), "+f"(d[22]), "+f"(d[23]), "+f"(d[24]), "+f"(d[25]), "+f"(d[26]), "+f"(d[27]), "+f"(d[28]), "+f"(d[29]), "+f"(d[30]), "+f"(d[31]) : "r"(a[0]), "r"(a[1]), "r"(a[2]), "r"(a[3]), "l"(db));
}
template <> DEV void wgmma_rs<48>(float* d, const u32* a, u64 db) {
  asm volatile("wgmma.mma_async.sync.aligned.m64n48k16.f32.bf16.bf16 {%0, %1, %2, %3, %4, %5, %6, %7, %8, %9, %10, %11, %12, %13, %14, %15, %16, %17, %18, %19, %20, %21, %22, %23}, {%24, %25, %26, %27}, %28, 1, 1, 1, 0;"
    : "+f"(d[0]), "+f"(d[1]), "+f"(d[2]), "+f"(d[3]), "+f"(d[4]), "+f"(d[5]), "+f"(d[6]), "+f"(d[7]), "+f"(d[8]), "+f"(d[9]), "+f"(d[10]), "+f"(d[11]), "+f"(d[12]), "+f"(d[13]), "+f"(d[14]), "+f"(d[15]), "+f"(d[16]), "+f"(d[17]), "+f"(d[18]), "+f"(d[19]), "+f"(d[20]), "+f"(d[21]), "+f"(d[22]), "+f"(d[23]) : "r"(a[0]), "r"(a[1]), "r"(a[2]), "r"(a[3]), "l"(db));
}
template <> DEV void wgmma_rs<32>(float* d, const u32* a, u64 db) {
  asm volatile("wgmma.mma_async.sync.aligned.m64n32k16.f32.bf16.bf16 {%0, %1, %2, %3, %4, %5, %6, %7, %8, %9, %10, %11, %12, %13, %14, %15}, {%16, %17, %18, %19}, %20, 1, 1, 1, 0;"
    : "+f"(d[0]), "+f"(d[1]), "+f"(d[2]), "+f"(d[3]), "+f"(d[4]), "+f"(d[5]), "+f"(d[6]), "+f"(d[7]), "+f"(d[8]), "+f"(d[9]), "+f"(d[10]), "+f"(d[11]), "+f"(d[12]), "+f"(d[13]), "+f"(d[14]), "+f"(d[15]) : "r"(a[0]), "r"(a[1]), "r"(a[2]), "r"(a[3]), "l"(db));
}
template <> DEV void wgmma_rs<16>(float* d, const u32* a, u64 db) {
  asm volatile("wgmma.mma_async.sync.aligned.m64n16k16.f32.bf16.bf16 {%0, %1, %2, %3, %4, %5, %6, %7}, {%8, %9, %10, %11}, %12, 1, 1, 1, 0;"
    : "+f"(d[0]), "+f"(d[1]), "+f"(d[2]), "+f"(d[3]), "+f"(d[4]), "+f"(d[5]), "+f"(d[6]), "+f"(d[7]) : "r"(a[0]), "r"(a[1]), "r"(a[2]), "r"(a[3]), "l"(db));
}

#define T_G 390
#define T_0 300
#define T_G2 300
#define ORDER (H4 ? 0xedcb8a957643210ull : 0xeb8dca957643210ull)
#define T_U0 4700
#define T_U1 4650
#define T_UP 1200
#define D_U 800
#define D_Y 2200
#define D_M 2000
#define D_H 1100
#define G_H 500
#define T_W 11000
#define G_W 500
#define R0 3
#define PROF0 0
#define SWAPWG 0
#define PROMO 2
#define T_X 0
#define T_PF 400
#define T_ZS 100
#define T_P 3000
#define T_P2 3900
#define D_Z 9700
#ifndef NV
#define NV 3
#endif
#define T_WO 3000
#define D_PB 0
#define T_R 3450
#define G_R 250
#define G_P 100
#define H4 0
#define RND0 0xf20
#define RND1 (H4 ? 0xf31 : 0xf431)
#define KX0 7
#define KX1 3
#define SPF 1
#define SPD 0
#define YG 3
#define D_Y3 1500
#define D_HG 0
#define G_S 280
#define G_S0 620
#define NP0 2
#define NP1 2
#define KZ0 2
#define KZ1 4
#define DKZ 2

template <int NW> DEV void phase_a(const Params& p, int j, int q, int role, int lane, u32 par) {
  const int o = lane & 3, cl = (8 * q + (lane >> 2)) * 2 * NW, c = 128 * j + 64 * (role & 1) + cl;
  const u32 ka = sb + j * KVP + o * 1024 + cl * 2;
  u32 sw[NW][4], k[11][NW], r[8][NW];
#pragma unroll
  for (int e = 0; e < NW; e++) lds128(sw[e], sb + SHK + c * 8 + e * 16);
#pragma unroll
  for (int i = 0; i < 11; i++) { if (NW == 2) lds64(k[i], ka + i * 128); else k[i][0] = lds32(ka + i * 128); }
#pragma unroll
  for (int i = 0; i < 8; i++) { if (NW == 2) lds64(r[i], ka + VO + i * 128); else r[i][0] = lds32(ka + VO + i * 128); }
  u16* dst = p.s->u + c * 2048 + 2040 - 32 * (role >> 1) - 8 * o;
#pragma unroll
  for (int e = 0; e < NW; e++) {
    const u32 w0 = prmt(sw[e][0], sw[e][2], 0x5410), w1 = prmt(sw[e][0], sw[e][2], 0x7632), w2 = prmt(sw[e][1], sw[e][3], 0x5410), w3 = prmt(sw[e][1], sw[e][3], 0x7632);
#pragma unroll
    for (int i = 0; i < 8; i++) r[i][e] = hmul2(hfma2(k[i + 3][e], w0, hfma2(k[i + 2][e], w1, hfma2(k[i + 1][e], w2, hmul2(k[i][e], w3)))), r[i][e]);
    r[7][e] = tagw(r[7][e], (o & 1) * 0x10001u, par);
    stg128(dst + e * 4096, make_uint4(prmt(r[7][e], r[6][e], 0x5410), prmt(r[5][e], r[4][e], 0x5410), prmt(r[3][e], r[2][e], 0x5410), prmt(r[1][e], r[0][e], 0x5410)));
    stg128(dst + e * 4096 + 2048, make_uint4(prmt(r[7][e], r[6][e], 0x7632), prmt(r[5][e], r[4][e], 0x7632), prmt(r[3][e], r[2][e], 0x7632), prmt(r[1][e], r[0][e], 0x7632)));
  }
}
template <int N, int STRIDE> DEV void shift_copy(u32 a, u32 dv, bool first) {
  uint4 w[N]; u32 pv[N];
#pragma unroll
  for (int i = 0; i < N; i++) { w[i] = lds128(a + i * STRIDE); pv[i] = lds32(a + i * STRIDE - 4); }
  if (first) { w[0].x = hadd2(w[0].x, dv); sts32(a, w[0].x); }
#pragma unroll
  for (int i = 0; i < N; i++)
    sts128(a + KO + i * STRIDE, make_uint4(prmt(pv[i], w[i].x, 0x5432), prmt(w[i].x, w[i].y, 0x5432), prmt(w[i].y, w[i].z, 0x5432), prmt(w[i].z, w[i].w, 0x5432)));
}
template <int S0, int S1> DEV void load_a(u32* a, u32 p) {
#pragma unroll
  for (int s = S0; s < S1; s++) { a[4 * s] = lds32(p + 256 * s); a[4 * s + 1] = lds32(p + 256 * s + 128); a[4 * s + 2] = lds32(p + 256 * s + 16); a[4 * s + 3] = lds32(p + 256 * s + 144); }
}
template <int S> DEV void load_a_if(u32* a, u32 p, bool c) {
  asm volatile("{\n.reg .pred q;\nsetp.ne.u32 q, %5, 0;\n@q ld.shared.b32 %0, [%4+%6];\n@q ld.shared.b32 %1, [%4+%7];\n@q ld.shared.b32 %2, [%4+%8];\n@q ld.shared.b32 %3, [%4+%9];\n}\n"
               : "+r"(a[4 * S]), "+r"(a[4 * S + 1]), "+r"(a[4 * S + 2]), "+r"(a[4 * S + 3])
               : "r"(p), "r"((u32)c), "n"(256 * S), "n"(256 * S + 128), "n"(256 * S + 16), "n"(256 * S + 144) : "memory");
}
template <int K> DEV void conv_pair(float* d, const u32* a, u32 lo) {
  wgmma_rs<256 - 32 * K>(d, a + 8 * K, desc_join(lo + 32 * K, 8u));
  wgmma_rs<240 - 32 * K>(d, a + 8 * K + 4, desc_join(lo + 32 * K + 16, 8u));
  wg_commit();
}
template <int K> DEV void conv_work(const float* d, u32* a, u32 ps, u32 pn, bool more) {
  constexpr int I = 7 - K;
  u32 pk[4];
  if constexpr (K >= R0) load_a_if<2 * (K - R0)>(a, pn, more);
#pragma unroll
  for (int e = 0; e < 4; e++) {
    const int nb = 4 * I + e;
    pk[e] = nb < 31 ? pack2(d[4 * nb] + d[(4 * nb + 6) & 127], d[4 * nb + 1] + d[(4 * nb + 7) & 127]) : pack2(d[4 * nb], d[4 * nb + 1]);
  }
  stsm4t(ps - 512 * I, pk);
  if constexpr (K >= R0) load_a_if<2 * (K - R0) + 1>(a, pn, more);
}
template <int NB> DEV int validate(u32 dst, const void* src, u32 bytes, bool fetched, u32 rbar, u32& rph, u32 off, u32 old) {
  int n = 0;
#pragma unroll 1
  while (true) {
    if (!fetched) { e_xload(dst, src, bytes, rbar); mbar_wait(rbar, rph); rph ^= 1; PROF(threadIdx.x == 288 && bytes > 12000, 122 + (bytes > 13000)); }
    fetched = false;
    u32 m = 1;
    const u32 a0 = dst + off, lim = a0 + bytes - 1024;
#pragma unroll 1
    for (u32 a = a0; a <= lim; a += NB * 1024) {
      u32 v[NB];
#pragma unroll
      for (int i = 0; i < NB; i++) v[i] = lds32(i < 4 ? a + i * 1024 : min(a + i * 1024, lim));
#pragma unroll
      for (int i = 0; i < NB; i += 2) m &= (v[i] ^ old) & (v[i + 1] ^ old);
    }
    if (__all_sync(0xffffffffu, m != 0)) break;
    trap_if_gt(++n, 1 << 16);
    RST(bytes >> 10);
  }
  return n;
}
DEV void ln_post(float (*c)[4], u32 a, int lane) {
  const bool o = lane & 4;
  if ((lane & 3) == (lane >> 3)) sts128(a, make_uint4(__float_as_uint(c[0][0]), __float_as_uint(o ? c[1][1] : c[1][0]), __float_as_uint(c[0][2]), __float_as_uint(o ? c[2][3] : c[2][2])));
}
DEV void ln_params(u32 a, u32* r2, u32* n2) {
  u32 v[8][4];
#pragma unroll
  for (int i = 0; i < 8; i++) lds128(v[i], a + i * 128);
#pragma unroll
  for (int hh = 0; hh < 2; hh++) {
    auto sum = [&](int e) { return ((__uint_as_float(v[0][e]) + __uint_as_float(v[1][e])) + (__uint_as_float(v[2][e]) + __uint_as_float(v[3][e]))) +
                                   ((__uint_as_float(v[4][e]) + __uint_as_float(v[5][e])) + (__uint_as_float(v[6][e]) + __uint_as_float(v[7][e]))); };
    const float mu = sum(2 * hh) * (1.f / 640.f), rs = rsq(fmaxf(sum(2 * hh + 1) * (1.f / 640.f) - mu * mu, 0.f) + 1e-5f);
    r2[hh] = pack2(rs, rs); n2[hh] = pack2(-mu * rs, -mu * rs);
  }
}
DEV void fetch_y(const Maps& tm, int j0, int j1, int role) {
  e_expect(bar(B_YF + (j0 > 0)), 4096 * (j1 - j0));
#pragma unroll 1
  for (int j = j0; j < j1; j++) e_tma2d(sb + YS + j * 4096, &tm.y, bar(B_YF + (j0 > 0)), 16 * (role & 3), (role >> 2) * 640 + 128 * j);
}
DEV float gelu2(float a) { return fmaf(a, tanh_fast(a * fmaf(0.035677408136300125f, a * a, 0.7978845608028654f)), a); }

template <int N>
DEV void g1_pass(float* acc, u32* zp, const u32* x1, int pass, int t128, u32* z2p, u32* xp, u32 ep) {
  constexpr int NG = N / 8, WG = N == 88, NPART = WG ? NP1 : NP0, PART = (NG + NPART - 1) / NPART, K0 = WG ? KZ1 : KZ0;
  constexpr u32 LB0 = WG ? desc_lo(sb + 16384, 1408) : desc_lo(sb, 8192), SIDE = (NPART == 2 ? 1 + (1 << DKZ) : 1) << K0;
  const int lane = t128 & 31;
  const u32 stop = pass ? 512 + SIDE : 512 + (WG ? (KX1 < 0 ? 0 : 1 << KX1) : 1 << KX0);
  auto put_x1 = [&]() {
#pragma unroll
    for (int i = 0; i < 20; i++) stg32((u32*)((size_t)xp ^ ((i & 2) << 4)) + (16 * (i >> 2) + ((i >> 1) & 1)) * 256 + (i & 1) * 32, x1[i]);
  };
  if (WG && KX1 == -1 && pass == 0) put_x1();
  u32 la = desc_lo(sb + XR, 1024), lb = LB0, bf = bar(B_FULL), bv = bar(B_VAL), par = 0, bprev = bar(B_DUMMY), kb = 0;
#pragma unroll 1
  do {
#pragma unroll 1
    do {
      mbar_wait(bv & ~7u, 0);
      mbar_wait(bf, par);
      PROF(kb == 0 && t128 == 0, WG ? 109 + pass : 40 + pass);
      wg_fence();
#pragma unroll
      for (int q = 0; q < 4; q++) {
        if constexpr (WG) wgmma_ss_88(acc, desc_join(la + q * 128, 8u), desc_join(lb + q * 176, 8u), kb | q);
        else wgmma_ss_128(acc, desc_join(la + q * 128, 8u), desc_join(lb + q * 128, 0x40000040u), kb | q);
      }
      wg_commit();
      const u32 bcur = bf + 8 * (B_EMPTY - B_FULL);
      kb = max(2 * kb, 1u);
      const bool wrap = kb == 16;
      par ^= wrap; bf = wrap ? bar(B_FULL) : bf + 8; bv += 4;
      la += 512; lb = wrap ? LB0 : lb + (BT >> 4);
      wg_wait<1>();
      mbar_arrive_if(bprev, t128 == 0);
      bprev = bcur;
    } while (!(kb & stop));
    if (kb != 512) {
      const int c = (lane + 2 * (t128 >> 5)) & 7;
      auto put = [&](int pt) {
#pragma unroll
        for (int n = pt * PART; n < (pt + 1) * PART && n < NG; n++) {
          const int gq = N == 128 ? 4 + n : n < 4 ? n : 16 + n;
          stg32(z2p + gq * 32, tagw(zp[2 * n], c == (gq & 7), ~ep));
          stg32(z2p + (27 + gq) * 32, tagw(zp[2 * n + 1], c == ((gq + 3) & 7), ~ep));
        }
        if (pt == NPART - 1) { __syncwarp(); mbar_arrive_if(bar(B_Z2D), lane == 0); PROF(t128 == 0, 107 + WG); }
      };
      if ((!WG || KX1 >= 0) && pass == 0) put_x1();
      else if (kb == 1 << K0) {
        mbar_wait(bar(B_ZS), 0);
        PROF(t128 == 0, WG ? 47 : 106);
        const u32 zsp = sb + M_ZS + (t128 >> 5) * 64 + (lane & 28), v0 = lds32(zsp), v1 = lds32(zsp + 32);
        const u32 r0 = prmt(v0, v0, 0x1010), n0 = prmt(v0, v0, 0x3232), r1 = prmt(v1, v1, 0x1010), n1 = prmt(v1, v1, 0x3232);
#pragma unroll
        for (int n = 0; n < NG; n++) { zp[2 * n] = hfma2(zp[2 * n], r0, n0); zp[2 * n + 1] = hfma2(zp[2 * n + 1], r1, n1); }
        put(0);
      } else if (NPART == 2) put(1);
    }
  } while (kb != 512);
  wg_wait<0>();
  mbar_arrive_if(bprev, t128 == 0);
  PROF(t128 == 0, WG ? 111 + pass : 43 + pass);
  if (WG && KX1 == -2 && pass == 0) put_x1();
}
template <int N>
DEV void g2_pass(float* acc, bool elect) {
  constexpr u32 ha = 0x40000040u, hb = 8;
  u32 s = 5, la = desc_lo(sb + AR, 16), lb = desc_lo(sb + 5 * BT + (N == 128 ? 0 : 2048), 3456), bf = bar(B_FULL + 5), bv = bar(B_ZV), par = 0, bprev = bar(B_DUMMY), k = 0;
#pragma unroll 1
  do {
    mbar_wait(bv, 0);
    mbar_wait(bf, par);
    PROF(k == 0 && elect, N == 88 ? 121 : 42);
    wg_fence();
#pragma unroll
    for (int q = 0; q < 4; q++) {
      if constexpr (N == 128) wgmma_ss_128(acc, desc_join(la + q * 2, ha), desc_join(lb + q * 432, hb), k | q);
      else wgmma_ss_88(acc, desc_join(la + q * 2, ha), desc_join(lb + q * 432, hb), k | q);
    }
    wg_commit();
    const u32 inc = s == 5 ? -5 : 1, bcur = bf + 8 * (B_EMPTY - B_FULL);
    par ^= s == 4; bf += 8 * inc; bv = min(bv + 8, bar(B_ZV + NV - 1)); k++;
    la += s == 4 ? -5 * 512 : 512; lb += inc * (BT >> 4); s += inc;
    wg_wait<1>();
    mbar_arrive_if(bprev, elect);
    bprev = bcur;
  } while (k < 32);
  wg_wait<0>();
}

DEV void spare_cta(const Params& p, const Maps& tm, int cq, int tid, int warp) {
  const int lane = tid & 31, kr = lane & 7, lg = lane >> 3, seg = warp % 3, kq = warp / 3;
  const u32 br = sb + M_BAR;
  e_init(br + 8 * warp, 1); e_init(br + 96 + 8 * warp, 1);
  const u32 ep = ld_rlx32(p.s->ctr);
  __syncthreads();
#define SPROF(i)
  until(clock(), SPD);
  auto release = [&](int f) {
    __syncthreads();
    if (tid == 0) { fence_gpu(); ctr_arrive(p.s->ctr, f, ep, tid); }
    SPROF(10 + f);
    __syncthreads();
  };
  const int ro = (cq & 1) * 3 + (cq >> 1) * 2 + lg, bx = seg < 2 ? seg : 2 + (ro >> 2), ck = seg < 2 ? lg : ro & 3;
#pragma unroll 1
  for (int pass = 0; pass < 2; pass++) {
    const int c0 = (pass ? 0 : 864) + 192 * cq;
    if (warp == 0) {
#pragma unroll 1
      for (int i = 0; i < 20; i++) {
        if ((i & 3) == 0) e_expect(br + 40 * pass + 2 * i, 32768);
        e_tma2d(sb + i * 8192, &tm.win32, br + 40 * pass + 8 * (i >> 2), (i & 2) ? c0 - 192 * cq + 768 + 32 * ((cq >> 1) + (i & 1)) : c0 + ((i & 1) ? 160 : 128 * pass), 128 * (i >> 2));
      }
    }
#pragma unroll 1
    for (int i = 0; i < 5; i++) {
      mbar_wait(br + 40 * pass + 8 * i, 0);
      SPROF(5 * pass + i);
      if (warp == 1 && SPF == 0) { e_pf3d(&tm.win, c0 + 32 - 32 * pass, 128 * i); e_pf3d(&tm.win, c0 + 32 - 32 * pass, 128 * i + 64); }
      if (seg < 2 || lg < 3) {
        uint4 v[4];
#pragma unroll
        for (int e = 0; e < 4; e++) v[e] = lds128(sb + i * 32768 + bx * 8192 + ((4 * e + kq) * 8 + kr) * 64 + ((ck ^ (kr >> 1)) << 4));
#pragma unroll
        for (int e = 0; e < 4; e++) stg128(p.s->ws + (((pass * 4 + cq) * 80 + 16 * i + 4 * e + kq) * 11 + seg * 4 + lg) * 64 + kr * 8, v[e]);
      }
    }
    if (warp == 1 && SPF == 1)
      for (int i = 0; i < 10; i++) e_pf3d(&tm.win, c0 + 32 - 32 * pass, 64 * i);
    release(I_WS + pass);
  }
  auto fetch = [&](int r) {
    const int c2 = (cq + r) & 3;
    e_expect(br + 96 + 8 * r, 69120);
#pragma unroll 1
    for (int e = 0; e < 9; e++) e_tma2d(sb + (r % 3) * 69120 + e * 7680, &tm.wout, br + 96 + 8 * r, 160 * cq, e < 8 ? 192 * c2 + 24 * e : 768 + 24 * c2);
  };
  if (warp == 0) { fetch(0); fetch(1); fetch(2); }
#pragma unroll 1
  for (int r = 0; r < 4; r++) {
    mbar_wait(br + 96 + 8 * r, 0);
    SPROF(13 + (r >> 1));
#pragma unroll 1
    for (int u = warp * 4 + lg; u < 135; u += 48) {
      const int gm = u / 5, be = u % 5, ps = gm < 6 || gm > 21 ? gm : gm < 16 ? gm + 6 : gm - 10, kg = r == 0 ? ps : ps < 12 ? 15 + 12 * r + ps : 36 + 15 * r + ps;
      const u32 a = sb + (r % 3) * 69120 + (gm * 8 + kr) * 320 + be * 64;
      const uint4 v0 = lds128(a), v1 = lds128(a + 16), v2 = lds128(a + 32), v3 = lds128(a + 48);
      u16* dst = p.s->wo + (cq * 540 + kg * 5 + be) * 256 + kr * 8;
      stg128(dst, make_uint4(v0.x, v1.x, v2.x, v3.x));
      stg128(dst + 64, make_uint4(v0.y, v1.y, v2.y, v3.y));
      stg128(dst + 128, make_uint4(v0.z, v1.z, v2.z, v3.z));
      stg128(dst + 192, make_uint4(v0.w, v1.w, v2.w, v3.w));
    }
    if (r == 0) { __syncthreads(); if (warp == 0) fetch(3); }
  }
  release(I_WO);
}

__global__ void __launch_bounds__(384, 1) mega_kernel(const __grid_constant__ Params p, const __grid_constant__ Maps tm) {
  extern __shared__ __align__(1024) unsigned char smem_raw[];
  const u32 t_start = clock();
  const int tid = threadIdx.x, warp = __shfl_sync(0xffffffffu, tid >> 5, 0), lane = tid & 31;
  int role;
  {
    u32 sm; asm volatile("mov.u32 %0, %%smid;" : "=r"(sm));
    const u32 x = sm - 64, q = (x * 4682u) >> 16;
    const u32 lo = ((sm + 14) & 14) * 8 + (sm >> 4) * 2, hi = ((x - 14 * q) & 14) * 8 + 8 + 2 * q;
    role = sm >= 124 ? sm - 4 : sm >= 120 ? sm + 8 : (sm < 64 ? lo : hi) + (sm & 1);
    role = __shfl_sync(0xffffffffu, role, 0);
  }
  if (role >= 128) { trap_if_gt(smem_u32(smem_raw) ^ sb, 0); spare_cta(p, tm, role - 128, tid, warp); return; }
  const int rt = role >> 2, cq = role & 3;

  e_init(bar(48 + warp), 2);
  if (warp == 8) {
    e_expect(bar(B_KV), KVP);
    e_tma2d(sb, &tm.k, bar(B_KV), 64 * (role & 1), 32 * (role >> 1) - 3);
    e_tma2d(sb + VO, &tm.v, bar(B_KV), 64 * (role & 1), 32 * (role >> 1));
    e_xload(sb + SHK, p.shk, 5120, bar(B_KV));
    PROF(lane == 0, 0);
  }
  if (warp < 6) e_tmpf(&tm.ssm + warp);
  e_init6(bar(warp), (u32)(0x111111a88882ull >> (4 * warp)) & 15);
  if (warp == 8) { e_expect(bar(B_SS), 4096); e_tma2d(sb + kslot(0), &tm.ssm, bar(B_SS), 0, 8 * role); PROF(lane == 0, 98); }
  if (tid < 63) {
    sts128(sb + (tid < 5 ? US + tid * UP + 4096 : tid < 15 ? kslot((tid - 5) >> 1) - 16 + (tid & 1) * KO : PWB + ((tid - 15) & 7) * PWP + ((tid - 15) >> 3) * 16), make_uint4(0, 0, 0, 0));
    fence_async_smem();
  }
  __syncthreads();

  if (warp < 8) {
    asm volatile("setmaxnreg.inc.sync.aligned.u32 224;");
    u32 dv;
    asm volatile("ld.global.nc.u16 %0, [%1];" : "=r"(dv) : "l"(p.ssmD + (tid & 128) + role));
    u32 ep = ld_rlx32(p.s->ctr);
    const int wg = warp >> 2, w = warp & 3, t128 = tid & 127, g = lane >> 2, t = lane & 3;
    const bool elect = t128 == 0;
    const u32 ts = __shfl_sync(0xffffffffu, t_start, 0);
    PROF(tid == 0, 1);
    {
      const u32 koff = sb + ((g & 1) ? 0 : KO) + 4 * (t + (g >> 1) - 3) + 32 * w;
      const u32 pw = sb + PWB + wg * 4 * PWP;
      u32 a[64];
      ep = __shfl_sync(0xffffffffu, ep, 0);
      consume(dv);
      if (wg) mbar_wait(bar(B_KV), 0);
#pragma unroll 1
      for (u32 js = wg ? RND1 : RND0; js != 15; js >>= 4) {
        const int j = js & 15;
        mbar_wait(bar(B_KV + j), 0);
        PROF(elect, j < 2 ? 2 + j : j == 2 ? 91 : j == 3 ? 126 : 93);
        phase_a<1>(p, j, w, role, lane_now(), (ep & 1) - 1);
        PROF(elect, j < 2 ? 4 + j : j == 2 ? 90 : j == 3 ? 127 : 79);
        if (j < 2) {
          mbar_wait(bar(B_SS + wg), 0);
          shift_copy<2, 2048>(sb + kslot(wg) + t128 * 16, dv, elect);
          bsync(1 + wg, 128);
          load_a<0, 16>(a, koff + kslot(wg));
          PROFD(elect, 6 + wg, a[63]);
        }
      }
#pragma unroll 1
      for (int ch = wg; ch < 5; ch += 2) {
        float d[128];
        const u32 pn = koff + kslot(ch + 2), ps = pw + w * (PWP + 32) + (255 - lane_now()) * 16, lo = desc_lo(sb + US + ch * UP, 16);
        const bool more = ch < 3;
        mbar_wait(bar(B_UV + ch), 0);
        if (ch > 0) bsync(3 + wg, 256);
        if (ch == 4) stamp_post(p.s->ctr, ep, S_Y, ts, lane_now() + w);
        PROF(elect, 8 + ch);
        wg_fence();
        conv_pair<0>(d, a, lo); conv_pair<1>(d, a, lo); conv_pair<2>(d, a, lo);
        if (R0 == 0 && more) mbar_wait(bar(B_KB + ch), 0);
        wg_wait<2>();
        mbar_arrive_if(bar(B_EMPTY) + 8 * (ch == 1 ? w >> 1 : ch - 1), w < ((H4 ? 0x12020 : 0x12040) >> (4 * ch) & 7) && lane_now() == 0);
        conv_work<0>(d, a, ps, pn, more); conv_pair<3>(d, a, lo);
        if (R0 == 1 && more) mbar_wait(bar(B_KB + ch), 0);
        wg_wait<2>(); conv_work<1>(d, a, ps, pn, more); conv_pair<4>(d, a, lo);
        if (R0 == 2 && more) mbar_wait(bar(B_KB + ch), 0);
        wg_wait<2>(); conv_work<2>(d, a, ps, pn, more); conv_pair<5>(d, a, lo); conv_pair<6>(d, a, lo); conv_pair<7>(d, a, lo);
        if (ch < 4) barrive(4 - wg, 256);
        if (R0 == 3 && more) mbar_wait(bar(B_KB + ch), 0);
        wg_wait<2>(); conv_work<3>(d, a, ps, pn, more); conv_work<4>(d, a, ps, pn, more); conv_work<5>(d, a, ps, pn, more);
        wg_wait<0>();
        PROFD(elect, 13 + ch, __float_as_uint(d[0]));
        conv_work<6>(d, a, ps, pn, more); conv_work<7>(d, a, ps, pn, more);
        bsync(1 + wg, 128);
        u32 q[2][4][4];
        const int t128 = 32 * w + lane_now();
#pragma unroll
        for (int h = 0; h < 2; h++)
#pragma unroll
          for (int i = 0; i < 4; i++) lds128(q[h][i], pw + i * PWP + h * 2048 + t128 * 16);
        if (more) load_a<16 - 2 * R0, 16>(a, pn);
        u16* yp = p.s->y + ((t128 >> 3) * 640 + 128 * ch + role) * 64 + ((t128 & 7) << 3);
#pragma unroll
        for (int h = 0; h < 2; h++) {
          u32 y[4];
#pragma unroll
          for (int e = 0; e < 4; e++) y[e] = hadd2(hadd2(q[h][0][e], q[h][1][e]), hadd2(q[h][2][e], q[h][3][e]));
          stg128(yp + h * (16 * 640 * 64), make_uint4(tagw(y[0], ~t128 & 1, ~ep), y[1], y[2], y[3]));
        }
        PROF(elect, 18 + ch);
      }
    }
    u32 zp[32], x1[5][4];
    u32* hp = (u32*)p.s->h2 + ((rt * 80 + 2 * warp) * 8 + 2 * cq) * 32 + lane;
    const u32 bs0 = hmul2((u32)__ldg(p.bsp + rt * 64 + 16 * w + g) * 0x10001u, 0x3f003f00u), bs1 = hmul2((u32)__ldg(p.bsp + rt * 64 + 16 * w + g + 8) * 0x10001u, 0x3f003f00u);
    {
      u32 x[5][4], S[5][2], C[5][2], r2[2], n2[2];
      float c[3][4];
      const u32 xa = sb + QS + wg * 2048 + (lane & 15) * 128 + (((2 * w + (lane >> 4)) ^ (lane & 7)) << 4);
      const u32 ya = sb + YS + (16 * warp + (lane >> 4) * 8 + (lane & 7)) * 32 + ((((lane >> 3) ^ (lane >> 2)) & 1) << 4);
      const u32 ma = sb + M_MOD + 64 * (warp >> 1) + 16 * t + 8 * (warp & 1), la = sb + M_LN + g * 16, par = (ep & 1) - 1;
      auto clear = [&]() {
#pragma unroll
        for (int i = 0; i < 12; i++) c[i >> 2][i & 3] = 0.f;
      };
      stg32((u32*)p.s->stz + role * 256 + tid, ep);
      mbar_wait(bar(B_Q), 0);
      PROF(elect, 23 + wg);
#pragma unroll
      for (int j = 0; j < 5; j++) ldsm4(x[j], xa + j * 4096);
      clear();
#pragma unroll
      for (int j = 0; j < 5; j++) row_stats(c, x[j]);
      ln_post(c, la + warp * 128, lane);
      bsync(5, 256);
      ln_params(la, r2, n2);
      u32 xn[5][4];
#pragma unroll
      for (int i = 0; i < 20; i++) xn[i >> 2][i & 3] = opaque(hfma2(x[i >> 2][i & 3], r2[i & 1], n2[i & 1]));
      PROFD(elect, 25 + wg, r2[0]);
#pragma unroll 1
      for (u32 ph = 0;; ph++) {
        u32 T[5][4], m = 1, bad = 0;
        mbar_wait(bar(B_YF + 2), ph & 1);
        PROF(elect && wg == 0 && ph == 0, 88);
#pragma unroll
        for (int j = 0; j < 5; j++) {
          u32 A[2], B[2], G[2];
          lds64(B, ma + j * 256); lds64(A, ma + j * 256 + 1280); lds64(G, ma + j * 256 + 2560); lds64(S[j], ma + j * 256 + 3840); lds64(C[j], ma + j * 256 + 5120);
#pragma unroll
          for (int i = 0; i < 2; i++) {
            m = min(min(min(m, A[i]), min(B[i], G[i])), min(S[j][i], C[j][i]));
            A[i] = hmul2(G[i], hadd2(A[i], ONE2)); B[i] = hmul2(G[i], B[i]); C[j][i] = hadd2(C[j][i], ONE2);
          }
#pragma unroll
          for (int i = 0; i < 4; i++) T[j][i] = hfma2(xn[j][i], A[i >> 1], B[i >> 1]);
        }
        clear();
#pragma unroll
        for (int j = 0; j < 5; j++) {
          u32 y[4];
          if (j == YG) PROFD(elect && ph == 0, 27 + wg, __float_as_uint(c[2][0]));
          if (j == 0 || j == YG) mbar_wait(bar(B_YF + (j > 0)), ph & 1);
          if (j == YG) tile_post(p.s->ctr + 32 + 32 * rt + cq, ts, ep, tid == 0);
          if (j == 0 || j == YG) PROF(elect && wg == 0 && ph == 0, j ? 92 : 89);
          ldsm4t(y, ya + j * 4096);
          bad |= (y[0] ^ par) | (y[2] ^ par);
#pragma unroll
          for (int i = 0; i < 4; i++) x1[j][i] = hfma2(y[i], T[j][i], x[j][i]);
          row_stats(c, x1[j]);
        }
        ln_post(c, la + 1024 + warp * 128, lane);
        PROFV(elect, 96, 100 * ph + 100);
        if (__all_sync(0xffffffffu, bsync_and(5, 256, m != 0 && (g != 0 || (bad & 0x10001) == 0)))) break;
        trap_if_gt(ph, 1 << 16);
        RST(__any_sync(0xffffffffu, m == 0) ? 1 : __any_sync(0xffffffffu, g == 0 && (bad & 0x10001)) ? 2 : 0);
        if (warp == 0) { fetch_y(tm, 0, YG, role); fetch_y(tm, YG, 5, role); e_xload(sb + M_MOD, p.s->mod, 6400, bar(B_YF + 2)); }
      }
      mbar_arrive_if(bar(B_HD), lane == 0);
      const u32 th = clock();
      ln_params(la + 1024, r2, n2);
      PROFD(elect, 29 + wg, r2[0]);
      const u32 m0 = (lane & 7) == 2 * cq, m1 = (lane & 7) == 2 * cq + 1;
#pragma unroll
      for (int j = 0; j < 5; j++) {
#pragma unroll
        for (int i = 0; i < 4; i++)
          stg32(hp + (16 * j + (i >> 1)) * 256 + (i & 1) * 32, tagw(hfma2(hfma2(x1[j][i], r2[i & 1], n2[i & 1]), C[j][i >> 1], S[j][i >> 1]), (i & 1) ? m1 : m0, par));
        if (j < 4) { until(th, G_S0 + j * G_S); __syncwarp(); }
      }
      PROF(elect, 31 + wg);
    }
    const int vg = wg ^ SWAPWG;
    float z[64];
    u32* z2p = (u32*)p.s->z2 + (role * 8 + 2 * w) * 27 * 32 + lane;
#pragma unroll 1
    for (int pass = 0; pass < 2; pass++) {
      if (vg == 0) g1_pass<128>(z, zp, x1[0], pass, t128, z2p, (u32*)((size_t)hp ^ ((w & 1) << 6)) + 32 * 80 * 8 * 32, ep);
      else g1_pass<88>(z, zp, x1[0], pass, t128, z2p, (u32*)((size_t)hp ^ ((w & 1) << 6)) + 32 * 80 * 8 * 32, ep);
      float st[4] = {0.f, 0.f, 0.f, 0.f};
      auto act = [&](int n0, int n1) {
#pragma unroll
        for (int i = 2 * n0; i < 2 * n1; i++) {
          const float u0 = gelu2(z[2 * i]), u1 = gelu2(z[2 * i + 1]);
          zp[i] = pack2(u0, u1);
          st[2 * (i & 1)] += u0 + u1; st[2 * (i & 1) + 1] = fmaf(u1, u1, fmaf(u0, u0, st[2 * (i & 1) + 1]));
        }
      };
      if (vg == 0) act(11, 16);
      act(0, 11);
      if (pass == 0) {
        const bool up = t & 2;
        float a = (up ? st[2] : st[0]) + shx(up ? st[0] : st[2], 2), q = (up ? st[3] : st[1]) + shx(up ? st[1] : st[3], 2);
        a += shx(a, 1); q += shx(q, 1);
        if (!(t & 1))
          asm volatile("st.relaxed.gpu.global.v2.b32 [%0], {%1,%2};" ::"l"(p.s->stz + (role * 64 + 16 * w + g + 4 * t) * 2 + vg), "f"(a), "r"(prmt(__float_as_uint(q), ep + 1, 0x3214)) : "memory");
        __syncwarp();
        mbar_arrive_if(bar(B_ZP), lane == 0);
      }
      PROFD(elect, 113 + 2 * pass + vg, zp[21]);
    }
    if (vg == 0) g2_pass<128>(z, elect); else g2_pass<88>(z, elect);
    PROFD(elect, 45 + vg, __float_as_uint(z[0]));
    {
      u32* Pp = (u32*)p.s->P + ((role * 27 + 6 * vg) * 8 + 2 * w) * 32 + lane;
      u32* Pq = Pp + (6 + 4 * vg) * 256;
      const u32 Ps = sb + ((6 * vg + (lane >> 4)) * 8 + 2 * w) * 128 + (lane & 15) * 16, Pt = Ps + (6 + 4 * vg) * 1024;
      const u32 m0 = (lane & 7) == 2 * w, m1 = (lane & 7) == 2 * w + 1;
      auto gate = [&](int n0, int n1) {
#pragma unroll
        for (int n = n0; n < n1; n++) {
          zp[2 * n] = tagw(hmul2(zp[2 * n], hfma2(pack2(z[4 * n], z[4 * n + 1]), 0x3f003f00u, bs0)), m0, ~ep);
          zp[2 * n + 1] = tagw(hmul2(zp[2 * n + 1], hfma2(pack2(z[4 * n + 2], z[4 * n + 3]), 0x3f003f00u, bs1)), m1, ~ep);
          if (n < 6) { stg32(Pp + n * 256, zp[2 * n]); stg32(Pp + n * 256 + 32, zp[2 * n + 1]); }
        }
      };
      auto put = [&](int n0, int n1) {
#pragma unroll
        for (int n = n0; n < n1; n++) { stg32(Pq + n * 256, zp[2 * n]); stg32(Pq + n * 256 + 32, zp[2 * n + 1]); }
      };
      gate(0, 11);
      if (vg == 0) gate(11, 16);
      bsync(5, 256);
      mbar_arrive_if(bar(B_PD), lane == 0);
#pragma unroll
      for (int n = 0; n < 10; n += 2) stsm4((n < 6 ? Ps : Pt) + n * 1024, zp + 2 * n);
      if (vg == 0) {
#pragma unroll
        for (int n = 10; n < 16; n += 2) stsm4(Pt + n * 1024, zp + 2 * n);
        fence_async_smem();
        barrive(5, 256);
        until(clock(), D_PB);
        __syncwarp();
        put(6, 16);
      } else {
        stsm2(sb + XR + 2 * w * 128 + (lane & 15) * 16, zp[20], zp[21]);
        fence_async_smem();
        put(6, 11);
      }
    }
    if (vg) {
      bsync(5, 256);
      PROF(elect, 48);
      float o[80];
      u32 la = desc_lo(sb, 1024), lb = desc_lo(sb + BT, 2560), bf = bar(B_WF), bprev = bar(B_DUMMY), par = 0, bv = bar(B_PV - 1), kb = 1, res[60];
#pragma unroll 1
      do {
        bool go;
        if (kb == 16) {
          mbar_wait(bar(B_RES), 0);
          const u32 ra = sb + RES + (t * 8 + 2 * w) * 128 + (g ^ (2 * t)) * 16;
          u32 all = 0;
#pragma unroll
          for (int e = 0; e < 15; e++) { lds128(res + 4 * e, e < 10 ? ra + (e >> 1) * 4096 + (e & 1) * 128 : sb + RES + 20480 + (e - 10) * 64 + t * 16); all ^= res[4 * e]; }
          consume(all);
          bsync(2, 128);
          mbar_arrive_if(bar(B_RD), elect);
        }
        if (kb >= 16) mbar_wait(bv, 0);
        mbar_wait(bf, par);
        PROF(elect && kb == 16, 49);
#pragma unroll 1
        do {
          wg_fence();
          wgmma_ss_160(o, desc_join(la, 8u), desc_join(lb, 8u), kb - 1);
          la += kb == 16 ? (XR >> 4) - 12 * 128 : 128;
          const u32 bcur = bf + 8 * (B_WE - B_WF);
          const bool wrap = kb & 0x2040;
          kb *= 2; par ^= wrap; bf += wrap ? -48 : 8; bv += (kb & 0xa550) ? 8 : 0;
          const bool t0 = mbar_test(bf, par), t1 = mbar_test(bv, 0);
          wgmma_ss_160(o, desc_join(la, 8u), desc_join(lb + 320, 8u), 1);
          wgmma_ss_160(o, desc_join(la + 128, 8u), desc_join(lb + 640, 8u), 1);
          wg_commit();
          go = __all_sync(0xffffffffu, t0 & (t1 | (kb < 16)) & !(kb & 0x40010));
          la += 256; lb += wrap ? -6 * (int)(WOST >> 4) : (int)(WOST >> 4);
          wg_wait<1>();
          mbar_arrive_if(bprev, elect);
          bprev = bcur;
          PROFG(elect, 33 - __clz(kb));
        } while (go);
      } while (kb != 0x40000);
      wg_wait<0>();
      PROFD(elect, 52, __float_as_uint(o[0]));
      u16* op = p.out + (rt * 64 + 16 * w + g) * 640 + 160 * cq + 8 * t;
#pragma unroll
      for (int i = 0; i < 10; i++) {
        const int be = i >> 1, h = i & 1;
        u32 r[4];
#pragma unroll
        for (int e = 0; e < 4; e++) r[e] = hfma2(pack2(o[16 * be + 4 * e + 2 * h], o[16 * be + 4 * e + 2 * h + 1]), res[40 + 4 * be + e], res[4 * i + e]);
        stg128(op + h * 8 * 640 + 32 * be, make_uint4(r[0], r[1], r[2], r[3]));
      }
      PROF(elect, 53);
    }
  } else {
    asm volatile("setmaxnreg.dec.sync.aligned.u32 56;");
    const int hw = warp - 8;
    if (hw == 0) {
      {
        const int n = lane < 15 ? (int)(ORDER >> (4 * lane)) & 15 : lane, j = n < 15 ? (n * 11) >> 5 : n < 20 ? n - 15 : n - 20, ty = n < 15 ? n - 3 * j : n < 20 ? 3 : 4;
        const int c0 = ty < 2 ? 128 * j + 64 * (role & 1) : ty == 2 ? 0 : ty == 3 ? 32 * role : 64 * j;
        const int c1 = ty < 2 ? 32 * (role >> 1) - 3 + 3 * ty : ty == 2 ? 1024 * j + 8 * role : ty == 3 ? 128 * j : 16 * role;
        const u32 dst = sb + (ty < 2 ? j * KVP + ty * VO : ty == 2 ? kslot(j) : ty == 3 ? WM + j * 8192 : QS + j * 2048);
        const u32 br = bar(ty < 2 ? B_KV + j : ty == 2 ? B_SS + j : ty == 3 ? B_WM + j : B_Q), bytes = ty == 0 ? VO : ty < 3 ? 4096 : ty == 3 ? 8192 : 2048;
        int due = T_0 + 3 * T_G;
#pragma unroll 1
        for (int i = 3; i < 30; i++) {
          until(t_start, due);
          if (lane == i) xtma2d(dst, &tm.k + ty, br, c0, c1, bytes);
          PROF(lane == i && (i < 4 || i == 29), 96 + lane);
          due += i < 15 ? T_G + (i == 14 ? T_X : 0) : i < 20 ? 2 * T_G2 : T_G2 / 2;
          __syncwarp();
        }
      }
      const u32 ep = ld_rlx32(p.s->ctr);
      int tz = 0;
      {
        ctr_poll(p.s->ctr, I_WS, ep, 4);
        PROF(lane == 0, 33);
        const u16* src = p.s->ws + cq * 56320;
#pragma unroll 1
        for (int r = 0; r < 4; r++) {
          if (r == 2) { mbar_wait(bar(B_WS1), 0); tz = lds32(sb + M_TZ); src += 3 * 56320; }
#pragma unroll 1
          for (int s = 0; s < 5; s++, src += 5632) {
            if (r == 0) until(t_start, T_W + s * G_W);
            w_g1(bar(B_EMPTY) + 8 * s, r & 1, bar(B_FULL) + 8 * s, sb + s * BT, &tm.win, (r < 2 ? 896 : 0) + 192 * cq, 64 * s + 320 * (r & 1), src);
            PROF(lane == 0 && r == 0, 74 + s); PROFG(lane == 0 && r == 2 * PG1 + 1, 21 + s);
          }
        }
      }
      e_expect(bar(B_FULL + 5), BT + 8192);
      e_tma2d(sb + AR, &tm.wsp, bar(B_FULL + 5), 0, 64 * rt);
      mbar_wait(bar(B_Z2D), 0);
      fence_gpu();
      ctr_arrive(p.s->ctr, I_Z2, ep, lane);
      PROF(lane == 0, 36);
      until(t_start, tz + D_Z);
      PROF(lane == 0, 35);
      {
        const u16* src = p.s->z2 + cq * (BT / 2);
        u32 par = 0;
#pragma unroll 1
        for (int c0 = 0;; par ^= 1) {
#pragma unroll
          for (int e = 0; e < 6; e++, c0 += 64, src += 2 * BT) {
            const int s = (e + 5) % 6;
            if (e == 2 && c0 == 2048) break;
            if (e == 0 && c0 == 0) e_load(sb + s * BT, src, BT, bar(B_FULL + s)); else
            w_g2(bar(B_EMPTY + s), e ? par : par ^ 1, bar(B_FULL + s), sb + s * BT, src, sb + AR + e * 8192, &tm.wsp, c0, 64 * rt);
            if (e == NV - 1 && c0 < 384) { ctr_poll(p.s->ctr, I_Z2, ep, 128); PROF(lane == 0, 37); }
          }
          if (c0 == 2048) break;
        }
      }
      if (role == 0 && lane < 9) p.s->ctr[lane ? 15 - 8 * (ep & 1) + lane : 0] = lane ? 0 : ep + 1;
      if (role < 100 && lane < 16) stg32((u32*)p.s->mod + role * 16 + lane, 0);
      mbar_wait(bar(B_WO), 0);
      {
        const u16* src = p.s->wo + cq * 18 * (WOST / 2);
#pragma unroll 1
        for (int i = 0; i < 7; i++, src += WOST / 2) {
          w_load<WOST>(bar(B_EMPTY + 1) + 8 * ((i + 1) >> 1), 1, bar(B_WF) + 8 * i, sb + BT + i * WOST, src);
          stamp_post(p.s->ctr, ep, S_P, t_start, lane + i);
          if (i == 4) { e_expect(bar(B_RES), 20800); e_load(sb + RES, p.s->x1 + role * 10240, 20480, bar(B_RES)); e_load(sb + RES + 20480, p.s->mod + 3200 + 160 * cq, 320, bar(B_RES)); }
        }
        int due = stamp_wait(p.s->ctr, ep, S_P) + T_R;
#pragma unroll 1
        for (int r = 0; r < 2; r++) {
#pragma unroll 1
          for (int i = 0; i < 7 - 3 * r; i++, src += WOST / 2, due += G_R) { until(t_start, due); w_load<WOST>(bar(B_WE) + 8 * i, r, bar(B_WF) + 8 * i, sb + BT + i * WOST, src); }
        }
      }
    } else {
      u32 rph = 0, ep = ld_rlx32(p.s->ctr);
      if (hw == 1) {
        tile_wait(p.s->ctr + 32 + 32 * rt, ep - 1);
#pragma unroll 1
        for (int j = 0; j < 5; j++) {
          const int due = j ? T_U1 + j * T_UP : T_U0;
          until(t_start, due - D_U);
          if (!__all_sync(0xffffffffu, mbar_test(bar(B_KV + j), 0))) { mbar_wait(bar(B_KV + j), 0); until(clock(), D_U); }
          until(t_start, due);
          PROF(lane == 0, j ? 53 + j : 38);
          const int n = validate<4>(sb + US + j * UP, p.s->u + (128 * j + role) * 2048, 4096, false, bar(B_RF), rph, lane * 32, ep);
          if (n) RST(j ? j > 1 ? 3 + j : 3 : 10);
          e_arrive(bar(B_UV + j));
          PROF(lane == 0, 64 + j); PROFV(lane == 0, 69 + j, 100 * n + 100);
        }
        mbar_wait(bar(B_EMPTY + 3), 0);
        const int ty = stamp_wait(p.s->ctr, ep, S_Y);
        if (YG == 4) until(t_start, ty + D_Y3);
        fetch_y(tm, 0, YG, role);
        PROF(lane == 0, 58);
        until(t_start, ty + D_Y);
        fetch_y(tm, YG, 5, role);
        PROF(lane == 0, 59);
        {
          mbar_wait(bar(B_YF + 1), 0);
          const u32 t0 = t_start + max(tile_wait(p.s->ctr + 32 + 32 * rt, ep), ty + D_Y + D_HG);
          mbar_wait(bar(B_HD), 0);
#pragma unroll 1
          for (int j = 0; j < 5; j++) {
            until(t0, D_H + j * G_H);
            e_xload(sb + XR + j * 16384, p.s->h2 + (rt * 5 + j) * 8192, 16384, bar(B_SS + j));
            PROF(lane == 0 && j == 0, 60);
          }
        }
        const u32 t0 = clock();
#pragma unroll 1
        for (int i = 0; i < 16; i++) { until(t0, i * T_PF); e_prefetch(p.wsp + (role * 16 + i) * 2048, 4096); }
      } else {
        const int hi = hw - 2;
        const u32 ts = __shfl_sync(0xffffffffu, t_start, 0);
        const u32 d0 = __ldg(p.ssmD + 128 * min(lane, 4) + role);
        {
          const int ht = tid - 320, g = lane >> 2, t = lane & 3;
          u32 cv[5];
#pragma unroll
          for (int i = 0; i < 5; i++) cv[i] = __ldg((const u32*)p.c + ht + 64 * i);
#pragma unroll 1
          for (int i = 0; i < 5; i++) {
            const float a = bflo(cv[0]), b = bfhi(cv[0]);
            const u32 v = pack2(__fdividef(a, 1.f + __expf(-a)), __fdividef(b, 1.f + __expf(-b))), ad = sb + M_SC + i * 256 + hi * 128 + t * 32 + g * 2;
            sts16(ad, v); sts16(ad + 16, v >> 16);
#pragma unroll
            for (int j = 0; j < 4; j++) cv[j] = cv[j + 1];
          }
          sts32(sb + M_D + 4 * min(lane, 4), d0);
          __syncwarp();
        }
        ep = __shfl_sync(0xffffffffu, ep, 0);
        mbar_wait(bar(B_KV), 0);
#pragma unroll 1
        for (int j = 2; j < 5; j++) {
          const int lane = lane_now(), ht = 32 * hi + lane;
          if (H4 && j == 4) {
            mbar_wait(bar(B_KV + 4), 0);
            PROF(ht == 0, 93);
            phase_a<2>(p, 4, hi, role, lane, (opaque(ep) & 1) - 1);
            __syncwarp();
            e_arrive(bar(B_EMPTY + 1));
            PROF(ht == 0, 79);
          }
          mbar_wait(bar(B_SS + j), 0);
          shift_copy<4, 1024>(sb + kslot(j) + hi * 512 + lane_now() * 16, lds32(sb + M_D + 4 * j), hi + lane_now() == 0);
          __syncwarp();
          e_arrive(bar(B_KB + j - 2));
          PROF(ht == 0, 78 + j);
        }
        const int lane = lane_now(), ht = 32 * hi + lane, g = lane >> 2;
        {
          float acc[8] = {0.f, 0.f, 0.f, 0.f, 0.f, 0.f, 0.f, 0.f};
#pragma unroll 1
          for (int j = 0; j < 5; j++) {
            u32 cv[4], wv[8][4];
            mbar_wait(bar(B_WM + j), 0);
            if (j == 4) stamp_post(p.s->ctr, ep, S_MOD, ts, ht);
            PROF(ht == 0, 83 + j);
            lds128(cv, sb + M_SC + j * 256 + hi * 128 + g * 16);
#pragma unroll
            for (int i = 0; i < 8; i++) lds128(wv[i], sb + WM + j * 8192 + hi * 4096 + i * 512 + lane * 16);
#pragma unroll
            for (int i = 0; i < 8; i++) {
              const float c = (i & 1) ? bfhi(cv[i >> 1]) : bflo(cv[i >> 1]);
#pragma unroll
              for (int e = 0; e < 4; e++) { acc[2 * e] = fmaf(bflo(wv[i][e]), c, acc[2 * e]); acc[2 * e + 1] = fmaf(bfhi(wv[i][e]), c, acc[2 * e + 1]); }
            }
          }
          const u32 pa = sb + WM + hi * 4096;
          sts128(pa + lane * 32, make_uint4(__float_as_uint(acc[0]), __float_as_uint(acc[1]), __float_as_uint(acc[2]), __float_as_uint(acc[3])));
          sts128(pa + lane * 32 + 16, make_uint4(__float_as_uint(acc[4]), __float_as_uint(acc[5]), __float_as_uint(acc[6]), __float_as_uint(acc[7])));
          bsync(6, 64);
          if (ht < 16) {
            float s[4] = {0.f, 0.f, 0.f, 0.f};
            const u32 ra = sb + WM + (role < 100 ? (ht & 3) * 32 + (ht >> 2) * 8 : ht * 8);
#pragma unroll
            for (int i = 0; i < 16; i++) { u32 v[2]; lds64(v, ra + (i >> 3) * 4096 + (i & 7) * 128); s[i & 2] += __uint_as_float(v[0]); s[(i & 2) + 1] += __uint_as_float(v[1]); }
            stg32((u32*)p.s->mod + role * 16 + ht, nz(pack2(s[0] + s[2], s[1] + s[3])));
          }
          __syncwarp();
          mbar_arrive_if(bar(B_EMPTY + 3), ht == 0);
          PROF(ht == 0, 39);
        }
        if (hi == 0) {
          until(ts, stamp_wait(p.s->ctr, ep, S_MOD) + D_M);
          PROF(lane == 0, 95);
          e_xload(sb + M_MOD, p.s->mod, 6400, bar(B_YF + 2));
        }
#pragma unroll 1
        for (int i = 0; i < 5; i++) {
          mbar_wait(bar(B_SS + i), 1);
          PROF(ht == 0 && i == 0, 61);
          const int n = validate<8>(sb + XR + i * 16384 + hi * 8192, p.s->h2 + (rt * 5 + i) * 8192 + hi * 4096, 8192, true, bar(B_RF + hw - 1), rph, lane * 32 + g * 4, ep);
          e_arrive(bar(B_VAL + i));
          if (i == 0) { e_arrive(bar(B_EMPTY + 4)); stamp_post(p.s->ctr, ep, S_Z, ts, ht); }
          PROF(ht == 0 && (i == 0 || i == 4), i ? 63 : 62); PROFV(ht == 0 && n, 97, 100 * i + 100);
        }
        if (hi == 0) ctr_poll(p.s->ctr, I_WS + 1, ep, 4); else sts32(sb + M_TZ, stamp_wait(p.s->ctr, ep, S_Z));
        e_arrive(bar(B_WS1));
        PROF(lane == 0, hi ? 119 : 34);
        {
          mbar_wait(bar(B_ZP), 0);
          until(clock(), T_ZS);
          float s, q;
          int n = 0;
#pragma unroll 1
          while (true) {
            uint4 v[4];
            u32 bad = 0;
#pragma unroll
            for (int i = 0; i < 4; i++) v[i] = ld_rlx128(p.s->stz + ((rt * 4 + i) * 64 + ht) * 2);
            s = 0.f; q = 0.f;
#pragma unroll
            for (int i = 0; i < 4; i++) {
              bad |= (v[i].y ^ (ep + 1)) | (v[i].w ^ (ep + 1));
              s += __uint_as_float(v[i].x) + __uint_as_float(v[i].z); q += __uint_as_float(v[i].y) + __uint_as_float(v[i].w);
            }
            if (__all_sync(0xffffffffu, (bad & 255) == 0)) break;
            trap_if_gt(++n, 1 << 20);
          }
          const float mu = s * (1.f / 864.f), rs = rsq(fmaxf(q * (1.f / 864.f) - mu * mu, 0.f) + 4e-5f);
          sts32(sb + M_ZS + ht * 4, pack2(rs, -mu * rs));
          __syncwarp();
          e_arrive(bar(B_ZS));
        }
      }
#pragma unroll 1
      for (int i = 0, s = 5; i < NV; i++) {
        mbar_wait(bar(B_FULL) + 8 * s, 0);
        PROF(hw == 1 && lane == 0 && i == 0, 117);
        const int n = validate<10>(sb + s * BT + (hw - 1) * 9216, p.s->z2 + (i * 4 + cq) * (BT / 2) + (hw - 1) * 4608, 9216, true, bar(B_RF + hw - 1), rph, lane_now() * 33 & ~3, ep);
        e_arrive(bar(B_ZV) + 8 * i);
        PROFV(lane == 0 && n, 118, 100 * i + 100);
        s = s == 5 ? 0 : s + 1;
      }
      if (hw == 1) { until(clock(), T_WO); ctr_poll(p.s->ctr, I_WO, ep, 4); e_arrive(bar(B_WO)); PROF(lane == 0, 94); }
      mbar_wait(bar(B_WF), 0);
      const int tp = stamp_wait(p.s->ctr, ep, S_P);
      mbar_wait(bar(B_PD), 0);
#pragma unroll 1
      for (int i = 0; i < 2; i++) {
        const u32 bytes = i ? 15360 : 12288;
        if (i) mbar_wait(bar(B_RD), 0);
        until(t_start, tp + (i ? T_P2 : T_P) + ((cq + hw) & 3) * G_P);
        PROF(hw == 1 && lane == 0, 100 + 2 * i);
        const int n = validate<8>(sb + XR + 1024 + i * 36864 + (hw - 1) * bytes, p.s->P + (rt * 4 + ((cq + hw) & 3)) * (BT / 2) + i * 6144, bytes, false,
                                  bar(B_RF + hw - 1), rph, lane_now() * 33 & ~3, ep);
        e_arrive(bar(B_PV + 3 * i) + 8 * (hw - 1));
        PROF(hw == 1 && lane == 0, 101 + 2 * i); PROFV(hw == 1 && lane == 0, 104 + i, 100 * n + 100);
      }
    }
  }
}

typedef CUresult (*EncodeFn)(CUtensorMap*, CUtensorMapDataType, cuuint32_t, void*, const cuuint64_t*, const cuuint64_t*, const cuuint32_t*,
                             const cuuint32_t*, CUtensorMapInterleave, CUtensorMapSwizzle, CUtensorMapL2promotion, CUtensorMapFloatOOBfill);

extern "C" void kernel_launch(void* const* d_in, const int* in_sizes, int n_in, void* d_out, int out_size) {
  static EncodeFn enc = nullptr;
  if (!enc) {
    void* fn = nullptr; cudaDriverEntryPointQueryResult st;
    cudaGetDriverEntryPoint("cuTensorMapEncodeTiled", &fn, cudaEnableDefault, &st);
    enc = (EncodeFn)fn;
    cudaFuncSetAttribute(mega_kernel, cudaFuncAttributeMaxDynamicSharedMemorySize, SMEM_BYTES);
  }
  Params p;
  p.shk = (const u16*)d_in[3]; p.ssmD = (const u16*)d_in[5];
  p.wsp = (const u16*)d_in[8]; p.bsp = (const u16*)d_in[9]; p.c = (const u16*)d_in[11];
  p.out = (u16*)d_out;
  cudaGetSymbolAddress((void**)&p.s, g_s);
  auto mk = [&](void* base, int rank, cuuint64_t d0, cuuint64_t d1, cuuint32_t b0, cuuint32_t b1, CUtensorMapSwizzle sw) {
    CUtensorMap m;
    cuuint64_t gd[3] = {d0, d1, 2}, gs[2] = {d0 * 2, 128};
    cuuint32_t bd[3] = {b0, b1, 2}, es[3] = {1, 1, 1};
    enc(&m, CU_TENSOR_MAP_DATA_TYPE_BFLOAT16, rank, base, gd, gs, bd, es, CU_TENSOR_MAP_INTERLEAVE_NONE, sw, (CUtensorMapL2promotion)PROMO,
        CU_TENSOR_MAP_FLOAT_OOB_FILL_NONE);
    return m;
  };
  Maps tm;
  tm.k = mk(d_in[1], 2, 640, 2048, 64, 35, CU_TENSOR_MAP_SWIZZLE_NONE);
  tm.v = mk(d_in[2], 2, 640, 2048, 64, 32, CU_TENSOR_MAP_SWIZZLE_NONE);
  tm.ssm = mk(d_in[4], 2, 256, 5120, 256, 8, CU_TENSOR_MAP_SWIZZLE_NONE);
  tm.wmod = mk(d_in[12], 2, 3840, 640, 32, 128, CU_TENSOR_MAP_SWIZZLE_NONE);
  tm.q = mk(d_in[0], 2, 640, 2048, 64, 16, CU_TENSOR_MAP_SWIZZLE_128B);
  tm.win = mk(d_in[7], 3, 1728, 640, 64, 64, CU_TENSOR_MAP_SWIZZLE_128B);
  tm.wsp = mk(d_in[8], 2, 2048, 2048, 64, 64, CU_TENSOR_MAP_SWIZZLE_128B);
  tm.y = mk(p.s->y, 2, 64, 20480, 16, 128, CU_TENSOR_MAP_SWIZZLE_32B);
  tm.win32 = mk(d_in[7], 2, 1728, 640, 32, 128, CU_TENSOR_MAP_SWIZZLE_64B);
  tm.wout = mk(d_in[10], 2, 640, 864, 160, 24, CU_TENSOR_MAP_SWIZZLE_NONE);
  mega_kernel<<<132, 384, SMEM_BYTES>>>(p, tm);
}
```

```cpp
#include <cuda_runtime.h>
#include <cuda.h>
#include <cuda_bf16.h>
#include <stdint.h>

typedef uint16_t u16; typedef uint32_t u32; typedef unsigned long long u64;
#define DEV __device__ __forceinline__

struct Scratch {
  u32 ctr[1280];
  u16 mod[4096];
  u64 stz[128 * 64 * 2];
  u16 u[640 * 2048];
  u16 y[32 * 640 * 64];
  u16 h2[32 * 80 * 8 * 64];
  u16 x1[32 * 80 * 8 * 64];
  u16 ws[2 * 4 * 80 * 11 * 64];
  u16 wo[4 * 108 * 20 * 64];
  u16 z2[32 * 4 * 8 * 27 * 64];
  u16 P[32 * 4 * 27 * 8 * 64];
};
__device__ __align__(1024) Scratch g_s;
enum { I_WS = 0, I_WO = 2, I_Z2 = 3 };
enum { S_Y = 0, S_MOD = 1, S_Z = 2, S_P = 3 };

struct Maps { CUtensorMap k, v, ssm, wmod, q, win, wsp, y, win32, wout; };
struct Params {
  Scratch* s;
  const u16 *shk, *ssmD, *c, *wsp, *bsp;
  u16* out;
};

constexpr u32 sb = 1024;
constexpr u32 BT = 27648, XR = 5 * BT, AR = 6 * BT, MISC = XR + 81920, SMEM_BYTES = 232448;
constexpr u32 M_LN = MISC, M_BAR = MISC + 2048, M_MOD = M_BAR + 1024, M_ZS = M_MOD + 7680, M_SM = M_ZS + 256, M_PROF = M_SM + 256;
constexpr u32 M_SC = M_MOD, M_TZ = M_SM, M_D = M_SM + 16, M_BS = M_PROF + 512;
constexpr u32 US = XR, UP = 4224, PWB = US + 5 * UP, PWP = 4192, YR = 2 * BT, KP = 8320, KO = 4144, WM = YR + 41984;
constexpr u32 KVP = 8576, VO = 4480, SHK = 5 * KVP, YS = XR - 20480, QS = XR + 55296, WOST = 15360, RES = AR + 16384, RES2 = AR + 49152;
DEV u32 kslot(int j) { return YR + 128 + j * KP; }
enum { B_WM = 0, B_RF = 5, B_SS = 8, B_PV = 13, B_YF = 19, B_RES = 22, B_FULL = 23, B_WO = 29, B_WS1 = 30, B_WF = 33, B_WE = 40,
       B_VAL = 48, B_KB = 53, B_KV = 56, B_EMPTY = 61, B_ZS = 71,
       B_DUMMY = 72, B_HD = 73, B_ZP = 74, B_PD = 75, B_Z2D = 76, B_Q = 77, B_UV = 78,
       B_ZV = 84 };
DEV constexpr u32 bar(int i) { return sb + M_BAR + 8 * i; }

#define RST(i)
#define PK(cond, i)
#define PROF(cond, i)
#define PROFD(cond, i, dep)
#define PROFV(cond, i, v)
#define PROFG(cond, i)

DEV u32 smem_u32(const void* p) { return (u32)__cvta_generic_to_shared(p); }
DEV void wg_fence() { asm volatile("wgmma.fence.sync.aligned;" ::: "memory"); }
DEV void wg_commit() { asm volatile("wgmma.commit_group.sync.aligned;" ::: "memory"); }
template <int N> DEV void wg_wait() { asm volatile("wgmma.wait_group.sync.aligned %0;" ::"n"(N) : "memory"); }
DEV u64 desc_join(u32 lo, u32 hi) { return ((u64)hi << 32) | lo; }
DEV constexpr u32 desc_lo(u32 addr, u32 lbo) { return ((addr & 0x3FFFF) >> 4) | ((lbo >> 4) << 16); }
DEV void mbar_init(u32 bar, int cnt) { asm volatile("mbarrier.init.shared::cta.b64 [%0], %1;" ::"r"(bar), "r"(cnt) : "memory"); }
DEV void mbar_arrive(u32 bar) { asm volatile("mbarrier.arrive.shared::cta.b64 _, [%0];" ::"r"(bar) : "memory"); }
DEV void mbar_arrive_if(u32 bar, bool c) { asm volatile("{\n.reg .pred p;\nsetp.ne.u32 p, %1, 0;\n@p mbarrier.arrive.shared::cta.b64 _, [%0];\n}\n" ::"r"(bar), "r"((u32)c) : "memory"); }
#define SAFE 0
#define SPIN(body) "W_LOOP:\n" body "@!p bra W_LOOP;\n"
DEV void mbar_wait(u32 bar, u32 parity) {
  asm volatile("{\n.reg .pred p, q;\n.reg .u32 n;\n" SPIN("mbarrier.try_wait.parity.shared::cta.b64 p, [%0], %1;\n") "}\n" ::"r"(bar), "r"(parity) : "memory");
}
DEV bool mbar_test(u32 bar, u32 parity) {
  u32 ok;
  asm volatile("{\n.reg .pred p;\nmbarrier.test_wait.parity.shared::cta.b64 p, [%1], %2;\nselp.u32 %0, 1, 0, p;\n}\n" : "=r"(ok) : "r"(bar), "r"(parity) : "memory");
  return ok;
}
DEV void trap_if_gt(int n, int lim) { asm volatile("{\n.reg .pred p;\nsetp.gt.s32 p, %0, %1;\n@p st.shared.u32 [%2], %0;\n}\n" ::"r"(n), "r"(lim), "r"(0x400000) : "memory"); }
DEV void until(u32 t0, int c) { while ((int)(clock() - t0) < c) {} }
DEV void bsync(int id, int n) { asm volatile("bar.sync %0, %1;" ::"r"(id), "r"(n) : "memory"); }
DEV bool bsync_and(int id, int n, bool v) {
  u32 r;
  asm volatile("{\n.reg .pred p, q;\nsetp.ne.u32 p, %3, 0;\nbarrier.red.and.aligned.pred q, %1, %2, p;\nselp.u32 %0, 1, 0, q;\n}\n" : "=r"(r) : "r"(id), "r"(n), "r"((u32)v) : "memory");
  return r;
}
DEV void barrive(int id, int n) { asm volatile("bar.arrive %0, %1;" ::"r"(id), "r"(n) : "memory"); }
DEV void fence_async_smem() { asm volatile("fence.proxy.async.shared::cta;" ::: "memory"); }
DEV void fence_gpu() { asm volatile("fence.acq_rel.gpu;" ::: "memory"); }
#define ELECT "{\n.reg .pred p;\nelect.sync _|p, 0xffffffff;\n"
DEV void e_init(u32 bar, int cnt) { asm volatile(ELECT "@p mbarrier.init.shared::cta.b64 [%0], %1;\n}\n" ::"r"(bar), "r"(cnt) : "memory"); }
DEV void e_init6(u32 b, int cnt) {
  asm volatile(ELECT "@p mbarrier.init.shared::cta.b64 [%0], 1;\n@p mbarrier.init.shared::cta.b64 [%0+96], 1;\n@p mbarrier.init.shared::cta.b64 [%0+192], 1;\n"
               "@p mbarrier.init.shared::cta.b64 [%0+288], 1;\n@p mbarrier.init.shared::cta.b64 [%0+480], 2;\n@p mbarrier.init.shared::cta.b64 [%0+576], %1;\n@p mbarrier.init.shared::cta.b64 [%0+672], 3;\n}\n" ::"r"(b), "r"(cnt) : "memory");
}
DEV void e_expect(u32 bar, u32 bytes) { asm volatile(ELECT "@p mbarrier.arrive.expect_tx.shared::cta.b64 _, [%0], %1;\n}\n" ::"r"(bar), "r"(bytes) : "memory"); }
DEV void e_arrive(u32 bar) { asm volatile(ELECT "@p mbarrier.arrive.shared::cta.b64 _, [%0];\n}\n" ::"r"(bar) : "memory"); }
DEV void e_load(u32 dst, const void* src, u32 bytes, u32 bar) {
  asm volatile(ELECT "@p cp.async.bulk.shared::cluster.global.mbarrier::complete_tx::bytes [%0], [%1], %2, [%3];\n}\n" ::"r"(dst), "l"(src), "r"(bytes), "r"(bar) : "memory");
}
DEV void e_xload(u32 dst, const void* src, u32 bytes, u32 bar) {
  asm volatile(ELECT "@p mbarrier.arrive.expect_tx.shared::cta.b64 _, [%3], %2;\n@p cp.async.bulk.shared::cluster.global.mbarrier::complete_tx::bytes [%0], [%1], %2, [%3];\n}\n"
               ::"r"(dst), "l"(src), "r"(bytes), "r"(bar) : "memory");
}
DEV void e_tma2d(u32 dst, const void* tm, u32 bar, int c0, int c1) {
  asm volatile(ELECT "@p cp.async.bulk.tensor.2d.shared::cluster.global.mbarrier::complete_tx::bytes [%0], [%1, {%3, %4}], [%2];\n}\n" ::"r"(dst), "l"(tm), "r"(bar), "r"(c0), "r"(c1) : "memory");
}
DEV void e_tma3d(u32 dst, const void* tm, u32 bar, int c0, int c1) {
  asm volatile(ELECT "@p cp.async.bulk.tensor.3d.shared::cluster.global.mbarrier::complete_tx::bytes [%0], [%1, {%3, %4, %5}], [%2];\n}\n" ::"r"(dst), "l"(tm), "r"(bar), "r"(c0), "r"(c1), "r"(0) : "memory");
}
DEV void e_pf3d(const void* tm, int c0, int c1) {
  asm volatile(ELECT "@p cp.async.bulk.prefetch.tensor.3d.L2.global [%0, {%1, %2, %3}];\n}\n" ::"l"(tm), "r"(c0), "r"(c1), "r"(0) : "memory");
}
#define WAIT_EXPECT "{\n.reg .pred p, q;\n.reg .u32 n;\n" SPIN("mbarrier.try_wait.parity.shared::cta.b64 p, [%0], %1;\n") \
  "elect.sync _|p, 0xffffffff;\n@p mbarrier.arrive.expect_tx.shared::cta.b64 _, [%2], %3;\n"
template <int BYTES> DEV void w_load(u32 be, u32 par, u32 bf, u32 dst, const void* src) {
  asm volatile(WAIT_EXPECT "@p cp.async.bulk.shared::cluster.global.mbarrier::complete_tx::bytes [%4], [%5], %3, [%2];\n}\n"
               ::"r"(be), "r"(par), "r"(bf), "n"(BYTES), "r"(dst), "l"(src) : "memory");
}
DEV void w_g1(u32 be, u32 par, u32 bf, u32 dst, const void* tm, int c0, int c1, const void* src) {
  asm volatile(WAIT_EXPECT "@p cp.async.bulk.tensor.3d.shared::cluster.global.mbarrier::complete_tx::bytes [%4], [%5, {%6, %7, %8}], [%2];\n"
               "@p cp.async.bulk.shared::cluster.global.mbarrier::complete_tx::bytes [%9], [%10], 11264, [%2];\n}\n"
               ::"r"(be), "r"(par), "r"(bf), "n"(BT), "r"(dst), "l"(tm), "r"(c0), "r"(c1), "r"(0), "r"(dst + 16384), "l"(src) : "memory");
}
DEV void w_g2(u32 be, u32 par, u32 bf, u32 db, const void* src, u32 da, const void* tm, int c0, int c1) {
  asm volatile(WAIT_EXPECT "@p cp.async.bulk.shared::cluster.global.mbarrier::complete_tx::bytes [%4], [%5], %10, [%2];\n"
               "@p cp.async.bulk.tensor.2d.shared::cluster.global.mbarrier::complete_tx::bytes [%6], [%7, {%8, %9}], [%2];\n}\n"
               ::"r"(be), "r"(par), "r"(bf), "n"(BT + 8192), "r"(db), "l"(src), "r"(da), "l"(tm), "r"(c0), "r"(c1), "n"(BT) : "memory");
}
DEV void load1d(u32 dst, const void* src, u32 bytes, u32 bar) {
  asm volatile("cp.async.bulk.shared::cluster.global.mbarrier::complete_tx::bytes [%0], [%1], %2, [%3];" ::"r"(dst), "l"(src), "r"(bytes), "r"(bar) : "memory");
}
DEV void pf2d(const void* tm, int c0, int c1) { asm volatile("cp.async.bulk.prefetch.tensor.2d.L2.global [%0, {%1, %2}];" ::"l"(tm), "r"(c0), "r"(c1) : "memory"); }
DEV void xtma2d(u32 dst, const void* tm, u32 bar, int c0, int c1, u32 bytes) {
  asm volatile("mbarrier.arrive.expect_tx.shared::cta.b64 _, [%2], %5;\ncp.async.bulk.tensor.2d.shared::cluster.global.mbarrier::complete_tx::bytes [%0], [%1, {%3, %4}], [%2];"
               ::"r"(dst), "l"(tm), "r"(bar), "r"(c0), "r"(c1), "r"(bytes) : "memory");
}
DEV void xload(u32 dst, const void* src, u32 bytes, u32 bar) {
  asm volatile("mbarrier.arrive.expect_tx.shared::cta.b64 _, [%3], %2;\ncp.async.bulk.shared::cluster.global.mbarrier::complete_tx::bytes [%0], [%1], %2, [%3];"
               ::"r"(dst), "l"(src), "r"(bytes), "r"(bar) : "memory");
}
DEV void e_prefetch(const void* src, u32 bytes) { asm volatile(ELECT "@p cp.async.bulk.prefetch.L2.global [%0], %1;\n}\n" ::"l"(src), "r"(bytes) : "memory"); }
DEV void e_tmpf(const void* tm) { asm volatile(ELECT "@p prefetch.tensormap [%0];\n}\n" ::"l"(tm) : "memory"); }
DEV uint4 ld_nc(const void* p) { uint4 v; asm volatile("ld.global.nc.v4.u32 {%0,%1,%2,%3}, [%4];" : "=r"(v.x), "=r"(v.y), "=r"(v.z), "=r"(v.w) : "l"(p)); return v; }
DEV void ldg128(u32* v, const void* p) { asm volatile("ld.global.cg.v4.u32 {%0,%1,%2,%3}, [%4];" : "=r"(v[0]), "=r"(v[1]), "=r"(v[2]), "=r"(v[3]) : "l"(p) : "memory"); }
DEV uint4 ld_rlx128(const void* p) {
  u64 a, b; asm volatile("ld.relaxed.gpu.global.v2.b64 {%0,%1}, [%2];" : "=l"(a), "=l"(b) : "l"(p) : "memory");
  return make_uint4((u32)a, (u32)(a >> 32), (u32)b, (u32)(b >> 32));
}
DEV uint2 ld_rlx64(const void* p) { u64 a; asm volatile("ld.relaxed.gpu.global.b64 %0, [%1];" : "=l"(a) : "l"(p) : "memory"); return make_uint2((u32)a, (u32)(a >> 32)); }
DEV void cp16(u32 dst, const void* src) { asm volatile("cp.async.cg.shared.global [%0], [%1], 16;" ::"r"(dst), "l"(src) : "memory"); }
DEV void cp_wait() { asm volatile("cp.async.wait_all;" ::: "memory"); }
DEV void bulk_store(void* dst, u32 src, u32 bytes) {
  asm volatile("cp.async.bulk.global.shared::cta.bulk_group [%0], [%1], %2;\ncp.async.bulk.commit_group;" ::"l"(dst), "r"(src), "r"(bytes) : "memory");
}
DEV void bulk_wait() { asm volatile("cp.async.bulk.wait_group 0;" ::: "memory"); }
DEV u32 ld_rlx32(const void* p) { u32 a; asm volatile("ld.relaxed.gpu.global.u32 %0, [%1];" : "=r"(a) : "l"(p) : "memory"); return a; }
DEV void ctr_arrive(u32* ctr, int f, u32 ep, u32 sel) {
  asm volatile("{\n.reg .pred p;\nsetp.eq.u32 p, %2, 0;\n@p red.relaxed.gpu.global.add.u32 [%0], %1;\n}\n"
               ::"l"(ctr + 1 + sel), "r"((1u - 2u * (ep & 1)) << (8 * f)), "r"(sel) : "memory");
}
DEV void ctr_poll(u32* ctr, int f, u32 ep, u32 n) {
  const u32 want = (ep & 1) ? 0 : n;
  int it = 0;
#pragma unroll 1
  while (__any_sync(0xffffffffu, ((ld_rlx32(ctr + 1) >> (8 * f)) & 255) != want)) trap_if_gt(++it, 1 << 20);
}
DEV void stamp_post(u32* ctr, u32 ep, int i, u32 t0, u32 sel) {
  asm volatile("{\n.reg .pred p;\nsetp.eq.u32 p, %2, 0;\n@p red.relaxed.gpu.global.max.u32 [%0+4], %1;\n@p red.relaxed.gpu.global.add.u32 [%0], 1;\n}\n"
               ::"l"(ctr + 8 + 8 * (ep & 1) + 2 * i + sel), "r"((u32)clock() - t0), "r"(sel) : "memory");
}
DEV int stamp_wait(u32* ctr, u32 ep, int i) {
  uint2 v = make_uint2(0, 0);
  int it = 0;
#pragma unroll 1
  while (__any_sync(0xffffffffu, v.x != 128)) { v = ld_rlx64(ctr + 8 + 8 * (ep & 1) + 2 * i); trap_if_gt(++it, 1 << 20); }
  return v.y;
}
DEV void tile_post(u32* w, u32 t0, u32 ep, bool c) { if (c) asm volatile("st.relaxed.gpu.global.u32 [%0], %1;" ::"l"(w), "r"(min((u32)clock() - t0, 0xfffffu) ^ ((ep + 1) << 20)) : "memory"); }
DEV int tile_wait(const u32* w, u32 ep) {
  u32 m;
  int it = 0;
#pragma unroll 1
  do {
    const uint2 a = ld_rlx64(w), b = ld_rlx64(w + 2);
    const u32 e = (ep + 1) << 20;
    m = max(max(a.x ^ e, a.y ^ e), max(b.x ^ e, b.y ^ e));
    trap_if_gt(++it, 1 << 20);
  } while (__any_sync(0xffffffffu, m >> 20));
  return m;
}
DEV void stg128(void* p, uint4 v) { asm volatile("st.global.v4.b32 [%0], {%1,%2,%3,%4};" ::"l"(p), "r"(v.x), "r"(v.y), "r"(v.z), "r"(v.w) : "memory"); }
DEV void stg32(void* p, u32 v) { asm volatile("st.global.b32 [%0], %1;" ::"l"(p), "r"(v) : "memory"); }
DEV void stg32_if(void* p, u32 v, bool c) { asm volatile("{\n.reg .pred q;\nsetp.ne.u32 q, %2, 0;\n@q st.global.b32 [%0], %1;\n}\n" ::"l"(p), "r"(v), "r"((u32)c) : "memory"); }
DEV u32 lds32(u32 a) { u32 v; asm volatile("ld.shared.b32 %0, [%1];" : "=r"(v) : "r"(a) : "memory"); return v; }
DEV void lds64(u32* v, u32 a) { asm volatile("ld.shared.v2.b32 {%0,%1}, [%2];" : "=r"(v[0]), "=r"(v[1]) : "r"(a) : "memory"); }
DEV uint4 lds128(u32 a) { uint4 v; asm volatile("ld.shared.v4.b32 {%0,%1,%2,%3}, [%4];" : "=r"(v.x), "=r"(v.y), "=r"(v.z), "=r"(v.w) : "r"(a) : "memory"); return v; }
DEV void lds128(u32* v, u32 a) { asm volatile("ld.shared.v4.b32 {%0,%1,%2,%3}, [%4];" : "=r"(v[0]), "=r"(v[1]), "=r"(v[2]), "=r"(v[3]) : "r"(a) : "memory"); }
DEV void sts16(u32 a, u32 v) { asm volatile("st.shared.b16 [%0], %1;" ::"r"(a), "h"((u16)v) : "memory"); }
DEV void sts32(u32 a, u32 v) { asm volatile("st.shared.b32 [%0], %1;" ::"r"(a), "r"(v) : "memory"); }
DEV void sts64f(u32 a, float x, float y) { asm volatile("st.shared.v2.f32 [%0], {%1,%2};" ::"r"(a), "f"(x), "f"(y) : "memory"); }
DEV void sts128(u32 a, uint4 v) { asm volatile("st.shared.v4.b32 [%0], {%1,%2,%3,%4};" ::"r"(a), "r"(v.x), "r"(v.y), "r"(v.z), "r"(v.w) : "memory"); }
DEV void consume(u32 x) { asm volatile("{\n.reg .pred p;\nsetp.eq.u32 p, %0, 0x7fc12345;\n@p nanosleep.u32 0;\n}\n" ::"r"(x) : "memory"); }
DEV int lane_now() { int l; asm volatile("mov.u32 %0, %%laneid;" : "=r"(l)); return l; }
DEV u32 opaque(u32 x) { asm volatile("" : "+r"(x)); return x; }
DEV void ldsm4(u32* r, u32 a) { asm volatile("ldmatrix.sync.aligned.m8n8.x4.shared.b16 {%0,%1,%2,%3}, [%4];" : "=r"(r[0]), "=r"(r[1]), "=r"(r[2]), "=r"(r[3]) : "r"(a) : "memory"); }
DEV void ldsm4t(u32* r, u32 a) { asm volatile("ldmatrix.sync.aligned.m8n8.x4.trans.shared.b16 {%0,%1,%2,%3}, [%4];" : "=r"(r[0]), "=r"(r[1]), "=r"(r[2]), "=r"(r[3]) : "r"(a) : "memory"); }
DEV void stsm4(u32 a, const u32* r) { asm volatile("stmatrix.sync.aligned.m8n8.x4.shared.b16 [%0], {%1,%2,%3,%4};" ::"r"(a), "r"(r[0]), "r"(r[1]), "r"(r[2]), "r"(r[3]) : "memory"); }
DEV void stsm4t(u32 a, const u32* r) { asm volatile("stmatrix.sync.aligned.m8n8.x4.trans.shared.b16 [%0], {%1,%2,%3,%4};" ::"r"(a), "r"(r[0]), "r"(r[1]), "r"(r[2]), "r"(r[3]) : "memory"); }
DEV void stsm2(u32 a, u32 r0, u32 r1) { asm volatile("stmatrix.sync.aligned.m8n8.x2.shared.b16 [%0], {%1,%2};" ::"r"(a), "r"(r0), "r"(r1) : "memory"); }
DEV void mma16816(float* c, u32 a0, u32 a1, u32 a2, u32 a3, u32 b0, u32 b1) {
  asm volatile("mma.sync.aligned.m16n8k16.row.col.f32.bf16.bf16.f32 {%0,%1,%2,%3}, {%4,%5,%6,%7}, {%8,%9}, {%0,%1,%2,%3};"
      : "+f"(c[0]), "+f"(c[1]), "+f"(c[2]), "+f"(c[3]) : "r"(a0), "r"(a1), "r"(a2), "r"(a3), "r"(b0), "r"(b1));
}
constexpr u32 ONE2 = 0x3f803f80u;
DEV u32 prmt(u32 a, u32 b, u32 s) { u32 r; asm("prmt.b32 %0, %1, %2, %3;" : "=r"(r) : "r"(a), "r"(b), "r"(s)); return r; }
DEV u32 hmul2(u32 a, u32 b) { u32 r; asm("mul.rn.bf16x2 %0, %1, %2;" : "=r"(r) : "r"(a), "r"(b)); return r; }
DEV u32 hadd2(u32 a, u32 b) { u32 r; asm("add.rn.bf16x2 %0, %1, %2;" : "=r"(r) : "r"(a), "r"(b)); return r; }
DEV u32 hfma2(u32 a, u32 b, u32 c) { u32 r; asm("fma.rn.bf16x2 %0, %1, %2, %3;" : "=r"(r) : "r"(a), "r"(b), "r"(c)); return r; }
DEV void row_stats(float (*c)[4], const u32* x) {
  mma16816(c[0], x[0], x[1], x[2], x[3], ONE2, ONE2);
  mma16816(c[1], x[0], x[1], x[2], x[3], x[0], x[2]);
  mma16816(c[2], x[0], x[1], x[2], x[3], x[1], x[3]);
}
DEV u32 pack2(float lo, float hi) { u32 r; asm("cvt.rn.bf16x2.f32 %0, %1, %2;" : "=r"(r) : "f"(hi), "f"(lo)); return r; }
DEV float bflo(u32 w) { return __uint_as_float(w * 65536u); }
DEV float bfhi(u32 w) { return __uint_as_float(w & 0xffff0000u); }
DEV u32 tagw(u32 w, u32 m, u32 par) { return (w & ~m) | (par & m); }
DEV u32 nz(u32 w) { return max(w, 1u); }
DEV float rsq(float x) { float r; asm("rsqrt.approx.ftz.f32 %0, %1;" : "=f"(r) : "f"(x)); return r; }
DEV float tanh_fast(float x) { float r; asm("tanh.approx.f32 %0, %1;" : "=f"(r) : "f"(x)); return r; }
DEV float shx(float v, int m) { return __shfl_xor_sync(0xffffffffu, v, m); }
DEV void wgmma_ss_128(float* d, u64 da, u64 db, int sd) {
  asm volatile("{\n.reg .pred p;\nsetp.ne.b32 p, %66, 0;\nwgmma.mma_async.sync.aligned.m64n128k16.f32.bf16.bf16 {%0, %1, %2, %3, %4, %5, %6, %7, %8, %9, %10, %11, %12, %13, %14, %15, %16, %17, %18, %19, %20, %21, %22, %23, %24, %25, %26, %27, %28, %29, %30, %31, %32, %33, %34, %35, %36, %37, %38, %39, %40, %41, %42, %43, %44, %45, %46, %47, %48, %49, %50, %51, %52, %53, %54, %55, %56, %57, %58, %59, %60, %61, %62, %63}, %64, %65, p, 1, 1, 0, 1;\n}\n"
    : "+f"(d[0]), "+f"(d[1]), "+f"(d[2]), "+f"(d[3]), "+f"(d[4]), "+f"(d[5]), "+f"(d[6]), "+f"(d[7]), "+f"(d[8]), "+f"(d[9]), "+f"(d[10]), "+f"(d[11]), "+f"(d[12]), "+f"(d[13]), "+f"(d[14]), "+f"(d[15]), "+f"(d[16]), "+f"(d[17]), "+f"(d[18]), "+f"(d[19]), "+f"(d[20]), "+f"(d[21]), "+f"(d[22]), "+f"(d[23]), "+f"(d[24]), "+f"(d[25]), "+f"(d[26]), "+f"(d[27]), "+f"(d[28]), "+f"(d[29]), "+f"(d[30]), "+f"(d[31]), "+f"(d[32]), "+f"(d[33]), "+f"(d[34]), "+f"(d[35]), "+f"(d[36]), "+f"(d[37]), "+f"(d[38]), "+f"(d[39]), "+f"(d[40]), "+f"(d[41]), "+f"(d[42]), "+f"(d[43]), "+f"(d[44]), "+f"(d[45]), "+f"(d[46]), "+f"(d[47]), "+f"(d[48]), "+f"(d[49]), "+f"(d[50]), "+f"(d[51]), "+f"(d[52]), "+f"(d[53]), "+f"(d[54]), "+f"(d[55]), "+f"(d[56]), "+f"(d[57]), "+f"(d[58]), "+f"(d[59]), "+f"(d[60]), "+f"(d[61]), "+f"(d[62]), "+f"(d[63]) : "l"(da), "l"(db), "r"(sd));
}
DEV void wgmma_ss_88(float* d, u64 da, u64 db, int sd) {
  asm volatile("{\n.reg .pred p;\nsetp.ne.b32 p, %46, 0;\nwgmma.mma_async.sync.aligned.m64n88k16.f32.bf16.bf16 {%0, %1, %2, %3, %4, %5, %6, %7, %8, %9, %10, %11, %12, %13, %14, %15, %16, %17, %18, %19, %20, %21, %22, %23, %24, %25, %26, %27, %28, %29, %30, %31, %32, %33, %34, %35, %36, %37, %38, %39, %40, %41, %42, %43}, %44, %45, p, 1, 1, 0, 1;\n}\n"
    : "+f"(d[0]), "+f"(d[1]), "+f"(d[2]), "+f"(d[3]), "+f"(d[4]), "+f"(d[5]), "+f"(d[6]), "+f"(d[7]), "+f"(d[8]), "+f"(d[9]), "+f"(d[10]), "+f"(d[11]), "+f"(d[12]), "+f"(d[13]), "+f"(d[14]), "+f"(d[15]), "+f"(d[16]), "+f"(d[17]), "+f"(d[18]), "+f"(d[19]), "+f"(d[20]), "+f"(d[21]), "+f"(d[22]), "+f"(d[23]), "+f"(d[24]), "+f"(d[25]), "+f"(d[26]), "+f"(d[27]), "+f"(d[28]), "+f"(d[29]), "+f"(d[30]), "+f"(d[31]), "+f"(d[32]), "+f"(d[33]), "+f"(d[34]), "+f"(d[35]), "+f"(d[36]), "+f"(d[37]), "+f"(d[38]), "+f"(d[39]), "+f"(d[40]), "+f"(d[41]), "+f"(d[42]), "+f"(d[43]) : "l"(da), "l"(db), "r"(sd));
}
DEV void wgmma_ss_160(float* d, u64 da, u64 db, int sd) {
  asm volatile("{\n.reg .pred p;\nsetp.ne.b32 p, %82, 0;\nwgmma.mma_async.sync.aligned.m64n160k16.f32.bf16.bf16 {%0, %1, %2, %3, %4, %5, %6, %7, %8, %9, %10, %11, %12, %13, %14, %15, %16, %17, %18, %19, %20, %21, %22, %23, %24, %25, %26, %27, %28, %29, %30, %31, %32, %33, %34, %35, %36, %37, %38, %39, %40, %41, %42, %43, %44, %45, %46, %47, %48, %49, %50, %51, %52, %53, %54, %55, %56, %57, %58, %59, %60, %61, %62, %63, %64, %65, %66, %67, %68, %69, %70, %71, %72, %73, %74, %75, %76, %77, %78, %79}, %80, %81, p, 1, 1, 0, 1;\n}\n"
    : "+f"(d[0]), "+f"(d[1]), "+f"(d[2]), "+f"(d[3]), "+f"(d[4]), "+f"(d[5]), "+f"(d[6]), "+f"(d[7]), "+f"(d[8]), "+f"(d[9]), "+f"(d[10]), "+f"(d[11]), "+f"(d[12]), "+f"(d[13]), "+f"(d[14]), "+f"(d[15]), "+f"(d[16]), "+f"(d[17]), "+f"(d[18]), "+f"(d[19]), "+f"(d[20]), "+f"(d[21]), "+f"(d[22]), "+f"(d[23]), "+f"(d[24]), "+f"(d[25]), "+f"(d[26]), "+f"(d[27]), "+f"(d[28]), "+f"(d[29]), "+f"(d[30]), "+f"(d[31]), "+f"(d[32]), "+f"(d[33]), "+f"(d[34]), "+f"(d[35]), "+f"(d[36]), "+f"(d[37]), "+f"(d[38]), "+f"(d[39]), "+f"(d[40]), "+f"(d[41]), "+f"(d[42]), "+f"(d[43]), "+f"(d[44]), "+f"(d[45]), "+f"(d[46]), "+f"(d[47]), "+f"(d[48]), "+f"(d[49]), "+f"(d[50]), "+f"(d[51]), "+f"(d[52]), "+f"(d[53]), "+f"(d[54]), "+f"(d[55]), "+f"(d[56]), "+f"(d[57]), "+f"(d[58]), "+f"(d[59]), "+f"(d[60]), "+f"(d[61]), "+f"(d[62]), "+f"(d[63]), "+f"(d[64]), "+f"(d[65]), "+f"(d[66]), "+f"(d[67]), "+f"(d[68]), "+f"(d[69]), "+f"(d[70]), "+f"(d[71]), "+f"(d[72]), "+f"(d[73]), "+f"(d[74]), "+f"(d[75]), "+f"(d[76]), "+f"(d[77]), "+f"(d[78]), "+f"(d[79]) : "l"(da), "l"(db), "r"(sd));
}
DEV void wgmma_rs_160(float* d, const u32* a, u64 db, int sd) {
  asm volatile("{\n.reg .pred p;\nsetp.ne.b32 p, %85, 0;\nwgmma.mma_async.sync.aligned.m64n160k16.f32.bf16.bf16 {%0, %1, %2, %3, %4, %5, %6, %7, %8, %9, %10, %11, %12, %13, %14, %15, %16, %17, %18, %19, %20, %21, %22, %23, %24, %25, %26, %27, %28, %29, %30, %31, %32, %33, %34, %35, %36, %37, %38, %39, %40, %41, %42, %43, %44, %45, %46, %47, %48, %49, %50, %51, %52, %53, %54, %55, %56, %57, %58, %59, %60, %61, %62, %63, %64, %65, %66, %67, %68, %69, %70, %71, %72, %73, %74, %75, %76, %77, %78, %79}, {%80, %81, %82, %83}, %84, p, 1, 1, 1;\n}\n"
    : "+f"(d[0]), "+f"(d[1]), "+f"(d[2]), "+f"(d[3]), "+f"(d[4]), "+f"(d[5]), "+f"(d[6]), "+f"(d[7]), "+f"(d[8]), "+f"(d[9]), "+f"(d[10]), "+f"(d[11]), "+f"(d[12]), "+f"(d[13]), "+f"(d[14]), "+f"(d[15]), "+f"(d[16]), "+f"(d[17]), "+f"(d[18]), "+f"(d[19]), "+f"(d[20]), "+f"(d[21]), "+f"(d[22]), "+f"(d[23]), "+f"(d[24]), "+f"(d[25]), "+f"(d[26]), "+f"(d[27]), "+f"(d[28]), "+f"(d[29]), "+f"(d[30]), "+f"(d[31]), "+f"(d[32]), "+f"(d[33]), "+f"(d[34]), "+f"(d[35]), "+f"(d[36]), "+f"(d[37]), "+f"(d[38]), "+f"(d[39]), "+f"(d[40]), "+f"(d[41]), "+f"(d[42]), "+f"(d[43]), "+f"(d[44]), "+f"(d[45]), "+f"(d[46]), "+f"(d[47]), "+f"(d[48]), "+f"(d[49]), "+f"(d[50]), "+f"(d[51]), "+f"(d[52]), "+f"(d[53]), "+f"(d[54]), "+f"(d[55]), "+f"(d[56]), "+f"(d[57]), "+f"(d[58]), "+f"(d[59]), "+f"(d[60]), "+f"(d[61]), "+f"(d[62]), "+f"(d[63]), "+f"(d[64]), "+f"(d[65]), "+f"(d[66]), "+f"(d[67]), "+f"(d[68]), "+f"(d[69]), "+f"(d[70]), "+f"(d[71]), "+f"(d[72]), "+f"(d[73]), "+f"(d[74]), "+f"(d[75]), "+f"(d[76]), "+f"(d[77]), "+f"(d[78]), "+f"(d[79]) : "r"(a[0]), "r"(a[1]), "r"(a[2]), "r"(a[3]), "l"(db), "r"(sd));
}
template <int N> DEV void wgmma_rs(float* d, const u32* a, u64 db);
template <> DEV void wgmma_rs<256>(float* d, const u32* a, u64 db) {
  asm volatile("wgmma.mma_async.sync.aligned.m64n256k16.f32.bf16.bf16 {%0, %1, %2, %3, %4, %5, %6, %7, %8, %9, %10, %11, %12, %13, %14, %15, %16, %17, %18, %19, %20, %21, %22, %23, %24, %25, %26, %27, %28, %29, %30, %31, %32, %33, %34, %35, %36, %37, %38, %39, %40, %41, %42, %43, %44, %45, %46, %47, %48, %49, %50, %51, %52, %53, %54, %55, %56, %57, %58, %59, %60, %61, %62, %63, %64, %65, %66, %67, %68, %69, %70, %71, %72, %73, %74, %75, %76, %77, %78, %79, %80, %81, %82, %83, %84, %85, %86, %87, %88, %89, %90, %91, %92, %93, %94, %95, %96, %97, %98, %99, %100, %101, %102, %103, %104, %105, %106, %107, %108, %109, %110, %111, %112, %113, %114, %115, %116, %117, %118, %119, %120, %121, %122, %123, %124, %125, %126, %127}, {%128, %129, %130, %131}, %132, 0, 1, 1, 0;"
    : "+f"(d[0]), "+f"(d[1]), "+f"(d[2]), "+f"(d[3]), "+f"(d[4]), "+f"(d[5]), "+f"(d[6]), "+f"(d[7]), "+f"(d[8]), "+f"(d[9]), "+f"(d[10]), "+f"(d[11]), "+f"(d[12]), "+f"(d[13]), "+f"(d[14]), "+f"(d[15]), "+f"(d[16]), "+f"(d[17]), "+f"(d[18]), "+f"(d[19]), "+f"(d[20]), "+f"(d[21]), "+f"(d[22]), "+f"(d[23]), "+f"(d[24]), "+f"(d[25]), "+f"(d[26]), "+f"(d[27]), "+f"(d[28]), "+f"(d[29]), "+f"(d[30]), "+f"(d[31]), "+f"(d[32]), "+f"(d[33]), "+f"(d[34]), "+f"(d[35]), "+f"(d[36]), "+f"(d[37]), "+f"(d[38]), "+f"(d[39]), "+f"(d[40]), "+f"(d[41]), "+f"(d[42]), "+f"(d[43]), "+f"(d[44]), "+f"(d[45]), "+f"(d[46]), "+f"(d[47]), "+f"(d[48]), "+f"(d[49]), "+f"(d[50]), "+f"(d[51]), "+f"(d[52]), "+f"(d[53]), "+f"(d[54]), "+f"(d[55]), "+f"(d[56]), "+f"(d[57]), "+f"(d[58]), "+f"(d[59]), "+f"(d[60]), "+f"(d[61]), "+f"(d[62]), "+f"(d[63]), "+f"(d[64]), "+f"(d[65]), "+f"(d[66]), "+f"(d[67]), "+f"(d[68]), "+f"(d[69]), "+f"(d[70]), "+f"(d[71]), "+f"(d[72]), "+f"(d[73]), "+f"(d[74]), "+f"(d[75]), "+f"(d[76]), "+f"(d[77]), "+f"(d[78]), "+f"(d[79]), "+f"(d[80]), "+f"(d[81]), "+f"(d[82]), "+f"(d[83]), "+f"(d[84]), "+f"(d[85]), "+f"(d[86]), "+f"(d[87]), "+f"(d[88]), "+f"(d[89]), "+f"(d[90]), "+f"(d[91]), "+f"(d[92]), "+f"(d[93]), "+f"(d[94]), "+f"(d[95]), "+f"(d[96]), "+f"(d[97]), "+f"(d[98]), "+f"(d[99]), "+f"(d[100]), "+f"(d[101]), "+f"(d[102]), "+f"(d[103]), "+f"(d[104]), "+f"(d[105]), "+f"(d[106]), "+f"(d[107]), "+f"(d[108]), "+f"(d[109]), "+f"(d[110]), "+f"(d[111]), "+f"(d[112]), "+f"(d[113]), "+f"(d[114]), "+f"(d[115]), "+f"(d[116]), "+f"(d[117]), "+f"(d[118]), "+f"(d[119]), "+f"(d[120]), "+f"(d[121]), "+f"(d[122]), "+f"(d[123]), "+f"(d[124]), "+f"(d[125]), "+f"(d[126]), "+f"(d[127]) : "r"(a[0]), "r"(a[1]), "r"(a[2]), "r"(a[3]), "l"(db));
}
template <> DEV void wgmma_rs<240>(float* d, const u32* a, u64 db) {
  asm volatile("wgmma.mma_async.sync.aligned.m64n240k16.f32.bf16.bf16 {%0, %1, %2, %3, %4, %5, %6, %7, %8, %9, %10, %11, %12, %13, %14, %15, %16, %17, %18, %19, %20, %21, %22, %23, %24, %25, %26, %27, %28, %29, %30, %31, %32, %33, %34, %35, %36, %37, %38, %39, %40, %41, %42, %43, %44, %45, %46, %47, %48, %49, %50, %51, %52, %53, %54, %55, %56, %57, %58, %59, %60, %61, %62, %63, %64, %65, %66, %67, %68, %69, %70, %71, %72, %73, %74, %75, %76, %77, %78, %79, %80, %81, %82, %83, %84, %85, %86, %87, %88, %89, %90, %91, %92, %93, %94, %95, %96, %97, %98, %99, %100, %101, %102, %103, %104, %105, %106, %107, %108, %109, %110, %111, %112, %113, %114, %115, %116, %117, %118, %119}, {%120, %121, %122, %123}, %124, 1, 1, 1, 0;"
    : "+f"(d[0]), "+f"(d[1]), "+f"(d[2]), "+f"(d[3]), "+f"(d[4]), "+f"(d[5]), "+f"(d[6]), "+f"(d[7]), "+f"(d[8]), "+f"(d[9]), "+f"(d[10]), "+f"(d[11]), "+f"(d[12]), "+f"(d[13]), "+f"(d[14]), "+f"(d[15]), "+f"(d[16]), "+f"(d[17]), "+f"(d[18]), "+f"(d[19]), "+f"(d[20]), "+f"(d[21]), "+f"(d[22]), "+f"(d[23]), "+f"(d[24]), "+f"(d[25]), "+f"(d[26]), "+f"(d[27]), "+f"(d[28]), "+f"(d[29]), "+f"(d[30]), "+f"(d[31]), "+f"(d[32]), "+f"(d[33]), "+f"(d[34]), "+f"(d[35]), "+f"(d[36]), "+f"(d[37]), "+f"(d[38]), "+f"(d[39]), "+f"(d[40]), "+f"(d[41]), "+f"(d[42]), "+f"(d[43]), "+f"(d[44]), "+f"(d[45]), "+f"(d[46]), "+f"(d[47]), "+f"(d[48]), "+f"(d[49]), "+f"(d[50]), "+f"(d[51]), "+f"(d[52]), "+f"(d[53]), "+f"(d[54]), "+f"(d[55]), "+f"(d[56]), "+f"(d[57]), "+f"(d[58]), "+f"(d[59]), "+f"(d[60]), "+f"(d[61]), "+f"(d[62]), "+f"(d[63]), "+f"(d[64]), "+f"(d[65]), "+f"(d[66]), "+f"(d[67]), "+f"(d[68]), "+f"(d[69]), "+f"(d[70]), "+f"(d[71]), "+f"(d[72]), "+f"(d[73]), "+f"(d[74]), "+f"(d[75]), "+f"(d[76]), "+f"(d[77]), "+f"(d[78]), "+f"(d[79]), "+f"(d[80]), "+f"(d[81]), "+f"(d[82]), "+f"(d[83]), "+f"(d[84]), "+f"(d[85]), "+f"(d[86]), "+f"(d[87]), "+f"(d[88]), "+f"(d[89]), "+f"(d[90]), "+f"(d[91]), "+f"(d[92]), "+f"(d[93]), "+f"(d[94]), "+f"(d[95]), "+f"(d[96]), "+f"(d[97]), "+f"(d[98]), "+f"(d[99]), "+f"(d[100]), "+f"(d[101]), "+f"(d[102]), "+f"(d[103]), "+f"(d[104]), "+f"(d[105]), "+f"(d[106]), "+f"(d[107]), "+f"(d[108]), "+f"(d[109]), "+f"(d[110]), "+f"(d[111]), "+f"(d[112]), "+f"(d[113]), "+f"(d[114]), "+f"(d[115]), "+f"(d[116]), "+f"(d[117]), "+f"(d[118]), "+f"(d[119]) : "r"(a[0]), "r"(a[1]), "r"(a[2]), "r"(a[3]), "l"(db));
}
template <> DEV void wgmma_rs<224>(float* d, const u32* a, u64 db) {
  asm volatile("wgmma.mma_async.sync.aligned.m64n224k16.f32.bf16.bf16 {%0, %1, %2, %3, %4, %5, %6, %7, %8, %9, %10, %11, %12, %13, %14, %15, %16, %17, %18, %19, %20, %21, %22, %23, %24, %25, %26, %27, %28, %29, %30, %31, %32, %33, %34, %35, %36, %37, %38, %39, %40, %41, %42, %43, %44, %45, %46, %47, %48, %49, %50, %51, %52, %53, %54, %55, %56, %57, %58, %59, %60, %61, %62, %63, %64, %65, %66, %67, %68, %69, %70, %71, %72, %73, %74, %75, %76, %77, %78, %79, %80, %81, %82, %83, %84, %85, %86, %87, %88, %89, %90, %91, %92, %93, %94, %95, %96, %97, %98, %99, %100, %101, %102, %103, %104, %105, %106, %107, %108, %109, %110, %111}, {%112, %113, %114, %115}, %116, 1, 1, 1, 0;"
    : "+f"(d[0]), "+f"(d[1]), "+f"(d[2]), "+f"(d[3]), "+f"(d[4]), "+f"(d[5]), "+f"(d[6]), "+f"(d[7]), "+f"(d[8]), "+f"(d[9]), "+f"(d[10]), "+f"(d[11]), "+f"(d[12]), "+f"(d[13]), "+f"(d[14]), "+f"(d[15]), "+f"(d[16]), "+f"(d[17]), "+f"(d[18]), "+f"(d[19]), "+f"(d[20]), "+f"(d[21]), "+f"(d[22]), "+f"(d[23]), "+f"(d[24]), "+f"(d[25]), "+f"(d[26]), "+f"(d[27]), "+f"(d[28]), "+f"(d[29]), "+f"(d[30]), "+f"(d[31]), "+f"(d[32]), "+f"(d[33]), "+f"(d[34]), "+f"(d[35]), "+f"(d[36]), "+f"(d[37]), "+f"(d[38]), "+f"(d[39]), "+f"(d[40]), "+f"(d[41]), "+f"(d[42]), "+f"(d[43]), "+f"(d[44]), "+f"(d[45]), "+f"(d[46]), "+f"(d[47]), "+f"(d[48]), "+f"(d[49]), "+f"(d[50]), "+f"(d[51]), "+f"(d[52]), "+f"(d[53]), "+f"(d[54]), "+f"(d[55]), "+f"(d[56]), "+f"(d[57]), "+f"(d[58]), "+f"(d[59]), "+f"(d[60]), "+f"(d[61]), "+f"(d[62]), "+f"(d[63]), "+f"(d[64]), "+f"(d[65]), "+f"(d[66]), "+f"(d[67]), "+f"(d[68]), "+f"(d[69]), "+f"(d[70]), "+f"(d[71]), "+f"(d[72]), "+f"(d[73]), "+f"(d[74]), "+f"(d[75]), "+f"(d[76]), "+f"(d[77]), "+f"(d[78]), "+f"(d[79]), "+f"(d[80]), "+f"(d[81]), "+f"(d[82]), "+f"(d[83]), "+f"(d[84]), "+f"(d[85]), "+f"(d[86]), "+f"(d[87]), "+f"(d[88]), "+f"(d[89]), "+f"(d[90]), "+f"(d[91]), "+f"(d[92]), "+f"(d[93]), "+f"(d[94]), "+f"(d[95]), "+f"(d[96]), "+f"(d[97]), "+f"(d[98]), "+f"(d[99]), "+f"(d[100]), "+f"(d[101]), "+f"(d[102]), "+f"(d[103]), "+f"(d[104]), "+f"(d[105]), "+f"(d[106]), "+f"(d[107]), "+f"(d[108]), "+f"(d[109]), "+f"(d[110]), "+f"(d[111]) : "r"(a[0]), "r"(a[1]), "r"(a[2]), "r"(a[3]), "l"(db));
}
template <> DEV void wgmma_rs<208>(float* d, const u32* a, u64 db) {
  asm volatile("wgmma.mma_async.sync.aligned.m64n208k16.f32.bf16.bf16 {%0, %1, %2, %3, %4, %5, %6, %7, %8, %9, %10, %11, %12, %13, %14, %15, %16, %17, %18, %19, %20, %21, %22, %23, %24, %25, %26, %27, %28, %29, %30, %31, %32, %33, %34, %35, %36, %37, %38, %39, %40, %41, %42, %43, %44, %45, %46, %47, %48, %49, %50, %51, %52, %53, %54, %55, %56, %57, %58, %59, %60, %61, %62, %63, %64, %65, %66, %67, %68, %69, %70, %71, %72, %73, %74, %75, %76, %77, %78, %79, %80, %81, %82, %83, %84, %85, %86, %87, %88, %89, %90, %91, %92, %93, %94, %95, %96, %97, %98, %99, %100, %101, %102, %103}, {%104, %105, %106, %107}, %108, 1, 1, 1, 0;"
    : "+f"(d[0]), "+f"(d[1]), "+f"(d[2]), "+f"(d[3]), "+f"(d[4]), "+f"(d[5]), "+f"(d[6]), "+f"(d[7]), "+f"(d[8]), "+f"(d[9]), "+f"(d[10]), "+f"(d[11]), "+f"(d[12]), "+f"(d[13]), "+f"(d[14]), "+f"(d[15]), "+f"(d[16]), "+f"(d[17]), "+f"(d[18]), "+f"(d[19]), "+f"(d[20]), "+f"(d[21]), "+f"(d[22]), "+f"(d[23]), "+f"(d[24]), "+f"(d[25]), "+f"(d[26]), "+f"(d[27]), "+f"(d[28]), "+f"(d[29]), "+f"(d[30]), "+f"(d[31]), "+f"(d[32]), "+f"(d[33]), "+f"(d[34]), "+f"(d[35]), "+f"(d[36]), "+f"(d[37]), "+f"(d[38]), "+f"(d[39]), "+f"(d[40]), "+f"(d[41]), "+f"(d[42]), "+f"(d[43]), "+f"(d[44]), "+f"(d[45]), "+f"(d[46]), "+f"(d[47]), "+f"(d[48]), "+f"(d[49]), "+f"(d[50]), "+f"(d[51]), "+f"(d[52]), "+f"(d[53]), "+f"(d[54]), "+f"(d[55]), "+f"(d[56]), "+f"(d[57]), "+f"(d[58]), "+f"(d[59]), "+f"(d[60]), "+f"(d[61]), "+f"(d[62]), "+f"(d[63]), "+f"(d[64]), "+f"(d[65]), "+f"(d[66]), "+f"(d[67]), "+f"(d[68]), "+f"(d[69]), "+f"(d[70]), "+f"(d[71]), "+f"(d[72]), "+f"(d[73]), "+f"(d[74]), "+f"(d[75]), "+f"(d[76]), "+f"(d[77]), "+f"(d[78]), "+f"(d[79]), "+f"(d[80]), "+f"(d[81]), "+f"(d[82]), "+f"(d[83]), "+f"(d[84]), "+f"(d[85]), "+f"(d[86]), "+f"(d[87]), "+f"(d[88]), "+f"(d[89]), "+f"(d[90]), "+f"(d[91]), "+f"(d[92]), "+f"(d[93]), "+f"(d[94]), "+f"(d[95]), "+f"(d[96]), "+f"(d[97]), "+f"(d[98]), "+f"(d[99]), "+f"(d[100]), "+f"(d[101]), "+f"(d[102]), "+f"(d[103]) : "r"(a[0]), "r"(a[1]), "r"(a[2]), "r"(a[3]), "l"(db));
}
template <> DEV void wgmma_rs<192>(float* d, const u32* a, u64 db) {
  asm volatile("wgmma.mma_async.sync.aligned.m64n192k16.f32.bf16.bf16 {%0, %1, %2, %3, %4, %5, %6, %7, %8, %9, %10, %11, %12, %13, %14, %15, %16, %17, %18, %19, %20, %21, %22, %23, %24, %25, %26, %27, %28, %29, %30, %31, %32, %33, %34, %35, %36, %37, %38, %39, %40, %41, %42, %43, %44, %45, %46, %47, %48, %49, %50, %51, %52, %53, %54, %55, %56, %57, %58, %59, %60, %61, %62, %63, %64, %65, %66, %67, %68, %69, %70, %71, %72, %73, %74, %75, %76, %77, %78, %79, %80, %81, %82, %83, %84, %85, %86, %87, %88, %89, %90, %91, %92, %93, %94, %95}, {%96, %97, %98, %99}, %100, 1, 1, 1, 0;"
    : "+f"(d[0]), "+f"(d[1]), "+f"(d[2]), "+f"(d[3]), "+f"(d[4]), "+f"(d[5]), "+f"(d[6]), "+f"(d[7]), "+f"(d[8]), "+f"(d[9]), "+f"(d[10]), "+f"(d[11]), "+f"(d[12]), "+f"(d[13]), "+f"(d[14]), "+f"(d[15]), "+f"(d[16]), "+f"(d[17]), "+f"(d[18]), "+f"(d[19]), "+f"(d[20]), "+f"(d[21]), "+f"(d[22]), "+f"(d[23]), "+f"(d[24]), "+f"(d[25]), "+f"(d[26]), "+f"(d[27]), "+f"(d[28]), "+f"(d[29]), "+f"(d[30]), "+f"(d[31]), "+f"(d[32]), "+f"(d[33]), "+f"(d[34]), "+f"(d[35]), "+f"(d[36]), "+f"(d[37]), "+f"(d[38]), "+f"(d[39]), "+f"(d[40]), "+f"(d[41]), "+f"(d[42]), "+f"(d[43]), "+f"(d[44]), "+f"(d[45]), "+f"(d[46]), "+f"(d[47]), "+f"(d[48]), "+f"(d[49]), "+f"(d[50]), "+f"(d[51]), "+f"(d[52]), "+f"(d[53]), "+f"(d[54]), "+f"(d[55]), "+f"(d[56]), "+f"(d[57]), "+f"(d[58]), "+f"(d[59]), "+f"(d[60]), "+f"(d[61]), "+f"(d[62]), "+f"(d[63]), "+f"(d[64]), "+f"(d[65]), "+f"(d[66]), "+f"(d[67]), "+f"(d[68]), "+f"(d[69]), "+f"(d[70]), "+f"(d[71]), "+f"(d[72]), "+f"(d[73]), "+f"(d[74]), "+f"(d[75]), "+f"(d[76]), "+f"(d[77]), "+f"(d[78]), "+f"(d[79]), "+f"(d[80]), "+f"(d[81]), "+f"(d[82]), "+f"(d[83]), "+f"(d[84]), "+f"(d[85]), "+f"(d[86]), "+f"(d[87]), "+f"(d[88]), "+f"(d[89]), "+f"(d[90]), "+f"(d[91]), "+f"(d[92]), "+f"(d[93]), "+f"(d[94]), "+f"(d[95]) : "r"(a[0]), "r"(a[1]), "r"(a[2]), "r"(a[3]), "l"(db));
}
template <> DEV void wgmma_rs<176>(float* d, const u32* a, u64 db) {
  asm volatile("wgmma.mma_async.sync.aligned.m64n176k16.f32.bf16.bf16 {%0, %1, %2, %3, %4, %5, %6, %7, %8, %9, %10, %11, %12, %13, %14, %15, %16, %17, %18, %19, %20, %21, %22, %23, %24, %25, %26, %27, %28, %29, %30, %31, %32, %33, %34, %35, %36, %37, %38, %39, %40, %41, %42, %43, %44, %45, %46, %47, %48, %49, %50, %51, %52, %53, %54, %55, %56, %57, %58, %59, %60, %61, %62, %63, %64, %65, %66, %67, %68, %69, %70, %71, %72, %73, %74, %75, %76, %77, %78, %79, %80, %81, %82, %83, %84, %85, %86, %87}, {%88, %89, %90, %91}, %92, 1, 1, 1, 0;"
    : "+f"(d[0]), "+f"(d[1]), "+f"(d[2]), "+f"(d[3]), "+f"(d[4]), "+f"(d[5]), "+f"(d[6]), "+f"(d[7]), "+f"(d[8]), "+f"(d[9]), "+f"(d[10]), "+f"(d[11]), "+f"(d[12]), "+f"(d[13]), "+f"(d[14]), "+f"(d[15]), "+f"(d[16]), "+f"(d[17]), "+f"(d[18]), "+f"(d[19]), "+f"(d[20]), "+f"(d[21]), "+f"(d[22]), "+f"(d[23]), "+f"(d[24]), "+f"(d[25]), "+f"(d[26]), "+f"(d[27]), "+f"(d[28]), "+f"(d[29]), "+f"(d[30]), "+f"(d[31]), "+f"(d[32]), "+f"(d[33]), "+f"(d[34]), "+f"(d[35]), "+f"(d[36]), "+f"(d[37]), "+f"(d[38]), "+f"(d[39]), "+f"(d[40]), "+f"(d[41]), "+f"(d[42]), "+f"(d[43]), "+f"(d[44]), "+f"(d[45]), "+f"(d[46]), "+f"(d[47]), "+f"(d[48]), "+f"(d[49]), "+f"(d[50]), "+f"(d[51]), "+f"(d[52]), "+f"(d[53]), "+f"(d[54]), "+f"(d[55]), "+f"(d[56]), "+f"(d[57]), "+f"(d[58]), "+f"(d[59]), "+f"(d[60]), "+f"(d[61]), "+f"(d[62]), "+f"(d[63]), "+f"(d[64]), "+f"(d[65]), "+f"(d[66]), "+f"(d[67]), "+f"(d[68]), "+f"(d[69]), "+f"(d[70]), "+f"(d[71]), "+f"(d[72]), "+f"(d[73]), "+f"(d[74]), "+f"(d[75]), "+f"(d[76]), "+f"(d[77]), "+f"(d[78]), "+f"(d[79]), "+f"(d[80]), "+f"(d[81]), "+f"(d[82]), "+f"(d[83]), "+f"(d[84]), "+f"(d[85]), "+f"(d[86]), "+f"(d[87]) : "r"(a[0]), "r"(a[1]), "r"(a[2]), "r"(a[3]), "l"(db));
}
template <> DEV void wgmma_rs<160>(float* d, const u32* a, u64 db) {
  asm volatile("wgmma.mma_async.sync.aligned.m64n160k16.f32.bf16.bf16 {%0, %1, %2, %3, %4, %5, %6, %7, %8, %9, %10, %11, %12, %13, %14, %15, %16, %17, %18, %19, %20, %21, %22, %23, %24, %25, %26, %27, %28, %29, %30, %31, %32, %33, %34, %35, %36, %37, %38, %39, %40, %41, %42, %43, %44, %45, %46, %47, %48, %49, %50, %51, %52, %53, %54, %55, %56, %57, %58, %59, %60, %61, %62, %63, %64, %65, %66, %67, %68, %69, %70, %71, %72, %73, %74, %75, %76, %77, %78, %79}, {%80, %81, %82, %83}, %84, 1, 1, 1, 0;"
    : "+f"(d[0]), "+f"(d[1]), "+f"(d[2]), "+f"(d[3]), "+f"(d[4]), "+f"(d[5]), "+f"(d[6]), "+f"(d[7]), "+f"(d[8]), "+f"(d[9]), "+f"(d[10]), "+f"(d[11]), "+f"(d[12]), "+f"(d[13]), "+f"(d[14]), "+f"(d[15]), "+f"(d[16]), "+f"(d[17]), "+f"(d[18]), "+f"(d[19]), "+f"(d[20]), "+f"(d[21]), "+f"(d[22]), "+f"(d[23]), "+f"(d[24]), "+f"(d[25]), "+f"(d[26]), "+f"(d[27]), "+f"(d[28]), "+f"(d[29]), "+f"(d[30]), "+f"(d[31]), "+f"(d[32]), "+f"(d[33]), "+f"(d[34]), "+f"(d[35]), "+f"(d[36]), "+f"(d[37]), "+f"(d[38]), "+f"(d[39]), "+f"(d[40]), "+f"(d[41]), "+f"(d[42]), "+f"(d[43]), "+f"(d[44]), "+f"(d[45]), "+f"(d[46]), "+f"(d[47]), "+f"(d[48]), "+f"(d[49]), "+f"(d[50]), "+f"(d[51]), "+f"(d[52]), "+f"(d[53]), "+f"(d[54]), "+f"(d[55]), "+f"(d[56]), "+f"(d[57]), "+f"(d[58]), "+f"(d[59]), "+f"(d[60]), "+f"(d[61]), "+f"(d[62]), "+f"(d[63]), "+f"(d[64]), "+f"(d[65]), "+f"(d[66]), "+f"(d[67]), "+f"(d[68]), "+f"(d[69]), "+f"(d[70]), "+f"(d[71]), "+f"(d[72]), "+f"(d[73]), "+f"(d[74]), "+f"(d[75]), "+f"(d[76]), "+f"(d[77]), "+f"(d[78]), "+f"(d[79]) : "r"(a[0]), "r"(a[1]), "r"(a[2]), "r"(a[3]), "l"(db));
}
template <> DEV void wgmma_rs<144>(float* d, const u32* a, u64 db) {
  asm volatile("wgmma.mma_async.sync.aligned.m64n144k16.f32.bf16.bf16 {%0, %1, %2, %3, %4, %5, %6, %7, %8, %9, %10, %11, %12, %13, %14, %15, %16, %17, %18, %19, %20, %21, %22, %23, %24, %25, %26, %27, %28, %29, %30, %31, %32, %33, %34, %35, %36, %37, %38, %39, %40, %41, %42, %43, %44, %45, %46, %47, %48, %49, %50, %51, %52, %53, %54, %55, %56, %57, %58, %59, %60, %61, %62, %63, %64, %65, %66, %67, %68, %69, %70, %71}, {%72, %73, %74, %75}, %76, 1, 1, 1, 0;"
    : "+f"(d[0]), "+f"(d[1]), "+f"(d[2]), "+f"(d[3]), "+f"(d[4]), "+f"(d[5]), "+f"(d[6]), "+f"(d[7]), "+f"(d[8]), "+f"(d[9]), "+f"(d[10]), "+f"(d[11]), "+f"(d[12]), "+f"(d[13]), "+f"(d[14]), "+f"(d[15]), "+f"(d[16]), "+f"(d[17]), "+f"(d[18]), "+f"(d[19]), "+f"(d[20]), "+f"(d[21]), "+f"(d[22]), "+f"(d[23]), "+f"(d[24]), "+f"(d[25]), "+f"(d[26]), "+f"(d[27]), "+f"(d[28]), "+f"(d[29]), "+f"(d[30]), "+f"(d[31]), "+f"(d[32]), "+f"(d[33]), "+f"(d[34]), "+f"(d[35]), "+f"(d[36]), "+f"(d[37]), "+f"(d[38]), "+f"(d[39]), "+f"(d[40]), "+f"(d[41]), "+f"(d[42]), "+f"(d[43]), "+f"(d[44]), "+f"(d[45]), "+f"(d[46]), "+f"(d[47]), "+f"(d[48]), "+f"(d[49]), "+f"(d[50]), "+f"(d[51]), "+f"(d[52]), "+f"(d[53]), "+f"(d[54]), "+f"(d[55]), "+f"(d[56]), "+f"(d[57]), "+f"(d[58]), "+f"(d[59]), "+f"(d[60]), "+f"(d[61]), "+f"(d[62]), "+f"(d[63]), "+f"(d[64]), "+f"(d[65]), "+f"(d[66]), "+f"(d[67]), "+f"(d[68]), "+f"(d[69]), "+f"(d[70]), "+f"(d[71]) : "r"(a[0]), "r"(a[1]), "r"(a[2]), "r"(a[3]), "l"(db));
}
template <> DEV void wgmma_rs<128>(float* d, const u32* a, u64 db) {
  asm volatile("wgmma.mma_async.sync.aligned.m64n128k16.f32.bf16.bf16 {%0, %1, %2, %3, %4, %5, %6, %7, %8, %9, %10, %11, %12, %13, %14, %15, %16, %17, %18, %19, %20, %21, %22, %23, %24, %25, %26, %27, %28, %29, %30, %31, %32, %33, %34, %35, %36, %37, %38, %39, %40, %41, %42, %43, %44, %45, %46, %47, %48, %49, %50, %51, %52, %53, %54, %55, %56, %57, %58, %59, %60, %61, %62, %63}, {%64, %65, %66, %67}, %68, 1, 1, 1, 0;"
    : "+f"(d[0]), "+f"(d[1]), "+f"(d[2]), "+f"(d[3]), "+f"(d[4]), "+f"(d[5]), "+f"(d[6]), "+f"(d[7]), "+f"(d[8]), "+f"(d[9]), "+f"(d[10]), "+f"(d[11]), "+f"(d[12]), "+f"(d[13]), "+f"(d[14]), "+f"(d[15]), "+f"(d[16]), "+f"(d[17]), "+f"(d[18]), "+f"(d[19]), "+f"(d[20]), "+f"(d[21]), "+f"(d[22]), "+f"(d[23]), "+f"(d[24]), "+f"(d[25]), "+f"(d[26]), "+f"(d[27]), "+f"(d[28]), "+f"(d[29]), "+f"(d[30]), "+f"(d[31]), "+f"(d[32]), "+f"(d[33]), "+f"(d[34]), "+f"(d[35]), "+f"(d[36]), "+f"(d[37]), "+f"(d[38]), "+f"(d[39]), "+f"(d[40]), "+f"(d[41]), "+f"(d[42]), "+f"(d[43]), "+f"(d[44]), "+f"(d[45]), "+f"(d[46]), "+f"(d[47]), "+f"(d[48]), "+f"(d[49]), "+f"(d[50]), "+f"(d[51]), "+f"(d[52]), "+f"(d[53]), "+f"(d[54]), "+f"(d[55]), "+f"(d[56]), "+f"(d[57]), "+f"(d[58]), "+f"(d[59]), "+f"(d[60]), "+f"(d[61]), "+f"(d[62]), "+f"(d[63]) : "r"(a[0]), "r"(a[1]), "r"(a[2]), "r"(a[3]), "l"(db));
}
template <> DEV void wgmma_rs<112>(float* d, const u32* a, u64 db) {
  asm volatile("wgmma.mma_async.sync.aligned.m64n112k16.f32.bf16.bf16 {%0, %1, %2, %3, %4, %5, %6, %7, %8, %9, %10, %11, %12, %13, %14, %15, %16, %17, %18, %19, %20, %21, %22, %23, %24, %25, %26, %27, %28, %29, %30, %31, %32, %33, %34, %35, %36, %37, %38, %39, %40, %41, %42, %43, %44, %45, %46, %47, %48, %49, %50, %51, %52, %53, %54, %55}, {%56, %57, %58, %59}, %60, 1, 1, 1, 0;"
    : "+f"(d[0]), "+f"(d[1]), "+f"(d[2]), "+f"(d[3]), "+f"(d[4]), "+f"(d[5]), "+f"(d[6]), "+f"(d[7]), "+f"(d[8]), "+f"(d[9]), "+f"(d[10]), "+f"(d[11]), "+f"(d[12]), "+f"(d[13]), "+f"(d[14]), "+f"(d[15]), "+f"(d[16]), "+f"(d[17]), "+f"(d[18]), "+f"(d[19]), "+f"(d[20]), "+f"(d[21]), "+f"(d[22]), "+f"(d[23]), "+f"(d[24]), "+f"(d[25]), "+f"(d[26]), "+f"(d[27]), "+f"(d[28]), "+f"(d[29]), "+f"(d[30]), "+f"(d[31]), "+f"(d[32]), "+f"(d[33]), "+f"(d[34]), "+f"(d[35]), "+f"(d[36]), "+f"(d[37]), "+f"(d[38]), "+f"(d[39]), "+f"(d[40]), "+f"(d[41]), "+f"(d[42]), "+f"(d[43]), "+f"(d[44]), "+f"(d[45]), "+f"(d[46]), "+f"(d[47]), "+f"(d[48]), "+f"(d[49]), "+f"(d[50]), "+f"(d[51]), "+f"(d[52]), "+f"(d[53]), "+f"(d[54]), "+f"(d[55]) : "r"(a[0]), "r"(a[1]), "r"(a[2]), "r"(a[3]), "l"(db));
}
template <> DEV void wgmma_rs<96>(float* d, const u32* a, u64 db) {
  asm volatile("wgmma.mma_async.sync.aligned.m64n96k16.f32.bf16.bf16 {%0, %1, %2, %3, %4, %5, %6, %7, %8, %9, %10, %11, %12, %13, %14, %15, %16, %17, %18, %19, %20, %21, %22, %23, %24, %25, %26, %27, %28, %29, %30, %31, %32, %33, %34, %35, %36, %37, %38, %39, %40, %41, %42, %43, %44, %45, %46, %47}, {%48, %49, %50, %51}, %52, 1, 1, 1, 0;"
    : "+f"(d[0]), "+f"(d[1]), "+f"(d[2]), "+f"(d[3]), "+f"(d[4]), "+f"(d[5]), "+f"(d[6]), "+f"(d[7]), "+f"(d[8]), "+f"(d[9]), "+f"(d[10]), "+f"(d[11]), "+f"(d[12]), "+f"(d[13]), "+f"(d[14]), "+f"(d[15]), "+f"(d[16]), "+f"(d[17]), "+f"(d[18]), "+f"(d[19]), "+f"(d[20]), "+f"(d[21]), "+f"(d[22]), "+f"(d[23]), "+f"(d[24]), "+f"(d[25]), "+f"(d[26]), "+f"(d[27]), "+f"(d[28]), "+f"(d[29]), "+f"(d[30]), "+f"(d[31]), "+f"(d[32]), "+f"(d[33]), "+f"(d[34]), "+f"(d[35]), "+f"(d[36]), "+f"(d[37]), "+f"(d[38]), "+f"(d[39]), "+f"(d[40]), "+f"(d[41]), "+f"(d[42]), "+f"(d[43]), "+f"(d[44]), "+f"(d[45]), "+f"(d[46]), "+f"(d[47]) : "r"(a[0]), "r"(a[1]), "r"(a[2]), "r"(a[3]), "l"(db));
}
template <> DEV void wgmma_rs<80>(float* d, const u32* a, u64 db) {
  asm volatile("wgmma.mma_async.sync.aligned.m64n80k16.f32.bf16.bf16 {%0, %1, %2, %3, %4, %5, %6, %7, %8, %9, %10, %11, %12, %13, %14, %15, %16, %17, %18, %19, %20, %21, %22, %23, %24, %25, %26, %27, %28, %29, %30, %31, %32, %33, %34, %35, %36, %37, %38, %39}, {%40, %41, %42, %43}, %44, 1, 1, 1, 0;"
    : "+f"(d[0]), "+f"(d[1]), "+f"(d[2]), "+f"(d[3]), "+f"(d[4]), "+f"(d[5]), "+f"(d[6]), "+f"(d[7]), "+f"(d[8]), "+f"(d[9]), "+f"(d[10]), "+f"(d[11]), "+f"(d[12]), "+f"(d[13]), "+f"(d[14]), "+f"(d[15]), "+f"(d[16]), "+f"(d[17]), "+f"(d[18]), "+f"(d[19]), "+f"(d[20]), "+f"(d[21]), "+f"(d[22]), "+f"(d[23]), "+f"(d[24]), "+f"(d[25]), "+f"(d[26]), "+f"(d[27]), "+f"(d[28]), "+f"(d[29]), "+f"(d[30]), "+f"(d[31]), "+f"(d[32]), "+f"(d[33]), "+f"(d[34]), "+f"(d[35]), "+f"(d[36]), "+f"(d[37]), "+f"(d[38]), "+f"(d[39]) : "r"(a[0]), "r"(a[1]), "r"(a[2]), "r"(a[3]), "l"(db));
}
template <> DEV void wgmma_rs<64>(float* d, const u32* a, u64 db) {
  asm volatile("wgmma.mma_async.sync.aligned.m64n64k16.f32.bf16.bf16 {%0, %1, %2, %3, %4, %5, %6, %7, %8, %9, %10, %11, %12, %13, %14, %15, %16, %17, %18, %19, %20, %21, %22, %23, %24, %25, %26, %27, %28, %29, %30, %31}, {%32, %33, %34, %35}, %36, 1, 1, 1, 0;"
    : "+f"(d[0]), "+f"(d[1]), "+f"(d[2]), "+f"(d[3]), "+f"(d[4]), "+f"(d[5]), "+f"(d[6]), "+f"(d[7]), "+f"(d[8]), "+f"(d[9]), "+f"(d[10]), "+f"(d[11]), "+f"(d[12]), "+f"(d[13]), "+f"(d[14]), "+f"(d[15]), "+f"(d[16]), "+f"(d[17]), "+f"(d[18]), "+f"(d[19]), "+f"(d[20]), "+f"(d[21]), "+f"(d[22]), "+f"(d[23]), "+f"(d[24]), "+f"(d[25]), "+f"(d[26]), "+f"(d[27]), "+f"(d[28]), "+f"(d[29]), "+f"(d[30]), "+f"(d[31]) : "r"(a[0]), "r"(a[1]), "r"(a[2]), "r"(a[3]), "l"(db));
}
template <> DEV void wgmma_rs<48>(float* d, const u32* a, u64 db) {
  asm volatile("wgmma.mma_async.sync.aligned.m64n48k16.f32.bf16.bf16 {%0, %1, %2, %3, %4, %5, %6, %7, %8, %9, %10, %11, %12, %13, %14, %15, %16, %17, %18, %19, %20, %21, %22, %23}, {%24, %25, %26, %27}, %28, 1, 1, 1, 0;"
    : "+f"(d[0]), "+f"(d[1]), "+f"(d[2]), "+f"(d[3]), "+f"(d[4]), "+f"(d[5]), "+f"(d[6]), "+f"(d[7]), "+f"(d[8]), "+f"(d[9]), "+f"(d[10]), "+f"(d[11]), "+f"(d[12]), "+f"(d[13]), "+f"(d[14]), "+f"(d[15]), "+f"(d[16]), "+f"(d[17]), "+f"(d[18]), "+f"(d[19]), "+f"(d[20]), "+f"(d[21]), "+f"(d[22]), "+f"(d[23]) : "r"(a[0]), "r"(a[1]), "r"(a[2]), "r"(a[3]), "l"(db));
}
template <> DEV void wgmma_rs<32>(float* d, const u32* a, u64 db) {
  asm volatile("wgmma.mma_async.sync.aligned.m64n32k16.f32.bf16.bf16 {%0, %1, %2, %3, %4, %5, %6, %7, %8, %9, %10, %11, %12, %13, %14, %15}, {%16, %17, %18, %19}, %20, 1, 1, 1, 0;"
    : "+f"(d[0]), "+f"(d[1]), "+f"(d[2]), "+f"(d[3]), "+f"(d[4]), "+f"(d[5]), "+f"(d[6]), "+f"(d[7]), "+f"(d[8]), "+f"(d[9]), "+f"(d[10]), "+f"(d[11]), "+f"(d[12]), "+f"(d[13]), "+f"(d[14]), "+f"(d[15]) : "r"(a[0]), "r"(a[1]), "r"(a[2]), "r"(a[3]), "l"(db));
}
template <> DEV void wgmma_rs<16>(float* d, const u32* a, u64 db) {
  asm volatile("wgmma.mma_async.sync.aligned.m64n16k16.f32.bf16.bf16 {%0, %1, %2, %3, %4, %5, %6, %7}, {%8, %9, %10, %11}, %12, 1, 1, 1, 0;"
    : "+f"(d[0]), "+f"(d[1]), "+f"(d[2]), "+f"(d[3]), "+f"(d[4]), "+f"(d[5]), "+f"(d[6]), "+f"(d[7]) : "r"(a[0]), "r"(a[1]), "r"(a[2]), "r"(a[3]), "l"(db));
}

#define T_G 390
#define T_0 300
#define T_G2 300
#define ORDER (H4 ? 0xedcb8a957643210ull : 0xeb8dca957643210ull)
#define T_U0 5000
#define T_U1 4650
#define T_UP 1200
#define D_U 800
#define D_Y 2200
#define D_M 2100
#define D_H 1100
#define G_H 500
#define T_W 12000
#define G_W 500
#define R0 3
#define PROF0 0
#define SWAPWG 0
#define PROMO 2
#define T_X 0
#define T_PF 400
#define T_ZS 100
#define T_P 2100
#define T_P2 3700
#define D_Z 9700
#ifndef NV
#define NV 3
#endif
#define T_WO 3000
#define KT 31
#define NR0 4
#define NR1 4
#define NH 4
#define WL 2
#define KP2 28
#define NPE 8
#define T_R 3100
#define G_R 250
#define G_P 40
#define H4 0
#define RND0 0xf20
#define RND1 (H4 ? 0xf31 : 0xf431)
#define KX0 8
#define KX1 5
#define SPF 1
#define SPD 0
#define YG 3
#define D_Y3 1500
#define D_HG 0
#define G_S 280
#define G_S0 620
#define NP0 2
#define NP1 2
#define KZ0 2
#define KZ1 4
#define DKZ 2

template <int NW> DEV void phase_a(const Params& p, int j, int q, int role, int lane, u32 par) {
  const int o = lane & 3, cl = (8 * q + (lane >> 2)) * 2 * NW, c = 128 * j + 64 * (role & 1) + cl;
  const u32 ka = sb + j * KVP + o * 1024 + cl * 2;
  u32 sw[NW][4], k[11][NW], r[8][NW];
#pragma unroll
  for (int e = 0; e < NW; e++) lds128(sw[e], sb + SHK + c * 8 + e * 16);
#pragma unroll
  for (int i = 0; i < 11; i++) { if (NW == 2) lds64(k[i], ka + i * 128); else k[i][0] = lds32(ka + i * 128); }
#pragma unroll
  for (int i = 0; i < 8; i++) { if (NW == 2) lds64(r[i], ka + VO + i * 128); else r[i][0] = lds32(ka + VO + i * 128); }
  u16* dst = p.s->u + c * 2048 + 2040 - 32 * (role >> 1) - 8 * o;
#pragma unroll
  for (int e = 0; e < NW; e++) {
    const u32 w0 = prmt(sw[e][0], sw[e][2], 0x5410), w1 = prmt(sw[e][0], sw[e][2], 0x7632), w2 = prmt(sw[e][1], sw[e][3], 0x5410), w3 = prmt(sw[e][1], sw[e][3], 0x7632);
#pragma unroll
    for (int i = 0; i < 8; i++) r[i][e] = hmul2(hfma2(k[i + 3][e], w0, hfma2(k[i + 2][e], w1, hfma2(k[i + 1][e], w2, hmul2(k[i][e], w3)))), r[i][e]);
    r[7][e] = tagw(r[7][e], (o & 1) * 0x10001u, par);
    stg128(dst + e * 4096, make_uint4(prmt(r[7][e], r[6][e], 0x5410), prmt(r[5][e], r[4][e], 0x5410), prmt(r[3][e], r[2][e], 0x5410), prmt(r[1][e], r[0][e], 0x5410)));
    stg128(dst + e * 4096 + 2048, make_uint4(prmt(r[7][e], r[6][e], 0x7632), prmt(r[5][e], r[4][e], 0x7632), prmt(r[3][e], r[2][e], 0x7632), prmt(r[1][e], r[0][e], 0x7632)));
  }
}
template <int N, int STRIDE> DEV void shift_copy(u32 a, u32 dv, bool first) {
  uint4 w[N]; u32 pv[N];
#pragma unroll
  for (int i = 0; i < N; i++) { w[i] = lds128(a + i * STRIDE); pv[i] = lds32(a + i * STRIDE - 4); }
  if (first) { w[0].x = hadd2(w[0].x, dv); sts32(a, w[0].x); }
#pragma unroll
  for (int i = 0; i < N; i++)
    sts128(a + KO + i * STRIDE, make_uint4(prmt(pv[i], w[i].x, 0x5432), prmt(w[i].x, w[i].y, 0x5432), prmt(w[i].y, w[i].z, 0x5432), prmt(w[i].z, w[i].w, 0x5432)));
}
template <int S0, int S1> DEV void load_a(u32* a, u32 p) {
#pragma unroll
  for (int s = S0; s < S1; s++) { a[4 * s] = lds32(p + 256 * s); a[4 * s + 1] = lds32(p + 256 * s + 128); a[4 * s + 2] = lds32(p + 256 * s + 16); a[4 * s + 3] = lds32(p + 256 * s + 144); }
}
template <int S> DEV void load_a_if(u32* a, u32 p, bool c) {
  asm volatile("{\n.reg .pred q;\nsetp.ne.u32 q, %5, 0;\n@q ld.shared.b32 %0, [%4+%6];\n@q ld.shared.b32 %1, [%4+%7];\n@q ld.shared.b32 %2, [%4+%8];\n@q ld.shared.b32 %3, [%4+%9];\n}\n"
               : "+r"(a[4 * S]), "+r"(a[4 * S + 1]), "+r"(a[4 * S + 2]), "+r"(a[4 * S + 3])
               : "r"(p), "r"((u32)c), "n"(256 * S), "n"(256 * S + 128), "n"(256 * S + 16), "n"(256 * S + 144) : "memory");
}
template <int K> DEV void conv_pair(float* d, const u32* a, u32 lo) {
  wgmma_rs<256 - 32 * K>(d, a + 8 * K, desc_join(lo + 32 * K, 8u));
  wgmma_rs<240 - 32 * K>(d, a + 8 * K + 4, desc_join(lo + 32 * K + 16, 8u));
  wg_commit();
}
template <int K> DEV void conv_work(const float* d, u32* a, u32 ps, u32 pn, bool more) {
  constexpr int I = 7 - K;
  u32 pk[4];
  if constexpr (K >= R0) load_a_if<2 * (K - R0)>(a, pn, more);
#pragma unroll
  for (int e = 0; e < 4; e++) {
    const int nb = 4 * I + e;
    pk[e] = nb < 31 ? pack2(d[4 * nb] + d[(4 * nb + 6) & 127], d[4 * nb + 1] + d[(4 * nb + 7) & 127]) : pack2(d[4 * nb], d[4 * nb + 1]);
  }
  stsm4t(ps - 512 * I, pk);
  if constexpr (K >= R0) load_a_if<2 * (K - R0) + 1>(a, pn, more);
}
template <int NB> DEV int validate(u32 bf, u32 par, u32 dst, u32 off, u32 old, u32 done, const void* src, u32 rbar, u32& rph) {
  int n = 0;
  const u32 a = opaque(dst + off);
  mbar_wait(bf, par);
  PROF(threadIdx.x == (NB == 8 ? 320 : 288) && (NB > 9 || done == bar(B_VAL) || done == bar(B_ZV)), NB == 8 ? 61 : NB == 9 ? 117 : 122 + (NB > 11));
#pragma unroll 1
  while (true) {
    u32 v[NB], m = 1;
#pragma unroll
    for (int i = 0; i < NB; i++) v[i] = lds32(a + i * 1024);
#pragma unroll
    for (int i = 0; i < NB; i++) asm("lop3.b32 %0, %0, %1, %2, 0x60;" : "+r"(m) : "r"(v[i]), "r"(old));
    const bool ok = __all_sync(0xffffffffu, m);
    mbar_arrive_if(done, ok && off == 0);
    if (ok) break;
    trap_if_gt(++n, 1 << 16);
    RST(NB);
    e_xload(dst, src, NB * 1024, rbar);
    mbar_wait(rbar, rph);
    rph ^= 1;
  }
  return n;
}
DEV void ln_post(float (*c)[4], u32 a, int lane) {
  const bool o = lane & 4;
  if ((lane & 3) == (lane >> 3)) sts128(a, make_uint4(__float_as_uint(c[0][0]), __float_as_uint(o ? c[1][1] : c[1][0]), __float_as_uint(c[0][2]), __float_as_uint(o ? c[2][3] : c[2][2])));
}
template <int NW> DEV void ln_params(u32 a, u32* r2, u32* n2) {
  u32 v[8][4];
#pragma unroll
  for (int i = 0; i < NW; i++) lds128(v[i], a + i * 128);
#pragma unroll
  for (int hh = 0; hh < 2; hh++) {
    auto sum4 = [&](int i, int e) { return (__uint_as_float(v[i][e]) + __uint_as_float(v[i + 1][e])) + (__uint_as_float(v[i + 2][e]) + __uint_as_float(v[i + 3][e])); };
    auto sum = [&](int e) { return NW == 8 ? sum4(0, e) + sum4(4, e) : sum4(0, e); };
    const float mu = sum(2 * hh) * (1.f / 640.f), rs = rsq(fmaxf(sum(2 * hh + 1) * (1.f / 640.f) - mu * mu, 0.f) + 1e-5f);
    r2[hh] = pack2(rs, rs); n2[hh] = pack2(-mu * rs, -mu * rs);
  }
}
DEV void fetch_y(const Maps& tm, int j0, int j1, int role) {
  e_expect(bar(B_YF + (j0 > 0)), 4096 * (j1 - j0));
#pragma unroll 1
  for (int j = j0; j < j1; j++) e_tma2d(sb + YS + j * 4096, &tm.y, bar(B_YF + (j0 > 0)), 16 * (role & 3), (role >> 2) * 640 + 128 * j);
}
DEV float gelu2(float a) { return fmaf(a, tanh_fast(a * fmaf(0.035677408136300125f, a * a, 0.7978845608028654f)), a); }

template <int N>
DEV void g1_pass(float* acc, u32* zp, const u32* x1, int pass, int t128, u32* z2p, u32* hp, u32 ep) {
  constexpr int NG = N / 8, WG = N == 88, NPART = WG ? NP1 : NP0, PART = (NG + NPART - 1) / NPART, K0 = WG ? KZ1 : KZ0;
  constexpr u32 LB0 = WG ? desc_lo(sb + 16384, 1408) : desc_lo(sb, 8192), SIDE = (NPART == 2 ? 1 + (1 << DKZ) : 1) << K0;
  const int lane = t128 & 31;
  const u32 stop = pass ? 512 + SIDE : 512 + (WG ? (KX1 < 0 ? 0 : 1 << KX1) : 1 << KX0) + (NH < 5);
  auto put_x1 = [&]() {
    u32* xp = (u32*)((size_t)hp ^ ((t128 & 32) << 1)) + 32 * 80 * 8 * 32;
#pragma unroll
    for (int i = 0; i < 20; i++) stg32((u32*)((size_t)xp ^ ((i & 2) << 4)) + (16 * (i >> 2) + ((i >> 1) & 1)) * 256 + (i & 1) * 32, x1[i]);
  };
  if (WG && KX1 == -1 && pass == 0) put_x1();
  u32 la = desc_lo(sb + XR, 1024), lb = LB0, bf = bar(B_FULL), bv = bar(B_VAL), par = 0, bprev = bar(B_DUMMY), kb = 0;
#pragma unroll 1
  do {
#pragma unroll 1
    do {
      mbar_wait(bv & ~7u, 0);
      mbar_wait(bf, par);
      PROF(kb == 0 && t128 == 0, WG ? 109 + pass : 40 + pass);
      wg_fence();
#pragma unroll
      for (int q = 0; q < 4; q++) {
        if constexpr (WG) wgmma_ss_88(acc, desc_join(la + q * 128, 8u), desc_join(lb + q * 176, 8u), kb | q);
        else wgmma_ss_128(acc, desc_join(la + q * 128, 8u), desc_join(lb + q * 128, 0x40000040u), kb | q);
      }
      wg_commit();
      const u32 bcur = bf + 8 * (B_EMPTY - B_FULL);
      kb = max(2 * kb, 1u);
      const bool wrap = kb == 16;
      par ^= wrap; bf = wrap ? bar(B_FULL) : bf + 8; bv += 4;
      la += 512; lb = wrap ? LB0 : lb + (BT >> 4);
      wg_wait<1>();
      mbar_arrive_if(bprev, t128 == 0);
      bprev = bcur;
    } while (!(kb & stop));
    if (kb != 512) {
      const int c = (lane + 2 * (t128 >> 5)) & 7;
      auto put = [&](int pt) {
#pragma unroll
        for (int n = pt * PART; n < (pt + 1) * PART && n < NG; n++) {
          const int gq = N == 128 ? 4 + n : n < 4 ? n : 16 + n;
          stg32(z2p + gq * 32, tagw(zp[2 * n], c == (gq & 7), ~ep));
          stg32(z2p + (27 + gq) * 32, tagw(zp[2 * n + 1], c == ((gq + 3) & 7), ~ep));
        }
        if (pt == NPART - 1) { __syncwarp(); mbar_arrive_if(bar(B_Z2D), lane == 0); PROF(t128 == 0, 107 + WG); }
      };
      if (NH < 5 && kb == 1) {
#pragma unroll
        for (int i = 4 * NH; i < 20; i++) stg32(hp + (16 * (i >> 2) + ((i >> 1) & 1)) * 256 + (i & 1) * 32, zp[i]);
      } else if ((!WG || KX1 >= 0) && pass == 0) put_x1();
      else if (kb == 1 << K0) {
        mbar_wait(bar(B_ZS), 0);
        PROF(t128 == 0, WG ? 47 : 106);
        const u32 zsp = sb + M_ZS + (t128 >> 5) * 64 + (lane & 28), v0 = lds32(zsp), v1 = lds32(zsp + 32);
        const u32 r0 = prmt(v0, v0, 0x1010), n0 = prmt(v0, v0, 0x3232), r1 = prmt(v1, v1, 0x1010), n1 = prmt(v1, v1, 0x3232);
#pragma unroll
        for (int n = 0; n < NG; n++) { zp[2 * n] = hfma2(zp[2 * n], r0, n0); zp[2 * n + 1] = hfma2(zp[2 * n + 1], r1, n1); }
        put(0);
      } else if (NPART == 2) put(1);
    }
  } while (kb != 512);
  wg_wait<0>();
  mbar_arrive_if(bprev, t128 == 0);
  PK(t128 == 0, WG ? 111 + pass : 43 + pass);
  if (WG && KX1 == -2 && pass == 0) put_x1();
}
template <int N>
DEV void g2_pass(float* acc, bool elect) {
  constexpr u32 ha = 0x40000040u, hb = 8;
  u32 s = 5, la = desc_lo(sb + AR, 16), lb = desc_lo(sb + 5 * BT + (N == 128 ? 0 : 2048), 3456), bf = bar(B_FULL + 5), bv = bar(B_ZV), par = 0, bprev = bar(B_DUMMY), k = 0;
#pragma unroll 1
  do {
    if (N == 128 && k == KP2) { wg_wait<0>(); mbar_arrive_if(bprev, elect); bprev = bar(B_DUMMY); bsync(3, 256); }
    mbar_wait(bv, 0);
    mbar_wait(bf, par);
    PROF(k == 0 && elect, N == 88 ? 121 : 42);
    wg_fence();
#pragma unroll
    for (int q = 0; q < 4; q++) {
      if constexpr (N == 128) wgmma_ss_128(acc, desc_join(la + q * 2, ha), desc_join(lb + q * 432, hb), k | q);
      else wgmma_ss_88(acc, desc_join(la + q * 2, ha), desc_join(lb + q * 432, hb), k | q);
    }
    wg_commit();
    const u32 inc = s == 5 ? -5 : 1, bcur = bf + 8 * (B_EMPTY - B_FULL);
    par ^= s == 4; bf += 8 * inc; bv = min(bv + 8, bar(B_ZV + NV - 1)); k++;
    la += s == 4 ? -5 * 512 : 512; lb += inc * (BT >> 4); s += inc;
    if (N == 88 && k == KT) barrive(3, 256);
    wg_wait<1>();
    mbar_arrive_if(bprev, elect);
    bprev = bcur;
  } while (k < 32);
  if (N == 128) { barrive(4, 256); bsync(7, 256); }
  wg_wait<0>();
  if (N == 88) barrive(7, 256);
}

DEV void spare_cta(const Params& p, const Maps& tm, int cq, int tid, int warp) {
  const int lane = tid & 31, kr = lane & 7, lg = lane >> 3, seg = warp % 3, kq = warp / 3;
  const u32 br = sb + M_BAR;
  e_init(br + 8 * warp, 1); e_init(br + 96 + 8 * warp, 1);
  const u32 ep = ld_rlx32(p.s->ctr);
  __syncthreads();
#define SPROF(i)
  until(clock(), SPD);
  auto release = [&](int f) {
    __syncthreads();
    if (tid == 0) { fence_gpu(); ctr_arrive(p.s->ctr, f, ep, tid); }
    SPROF(10 + f);
    __syncthreads();
  };
  const int ro = (cq & 1) * 3 + (cq >> 1) * 2 + lg, bx = seg < 2 ? seg : 2 + (ro >> 2), ck = seg < 2 ? lg : ro & 3;
#pragma unroll 1
  for (int pass = 0; pass < 2; pass++) {
    const int c0 = (pass ? 0 : 864) + 192 * cq;
    if (warp == 0) {
#pragma unroll 1
      for (int i = 0; i < 20; i++) {
        if ((i & 3) == 0) e_expect(br + 40 * pass + 2 * i, 32768);
        e_tma2d(sb + i * 8192, &tm.win32, br + 40 * pass + 8 * (i >> 2), (i & 2) ? c0 - 192 * cq + 768 + 32 * ((cq >> 1) + (i & 1)) : c0 + ((i & 1) ? 160 : 128 * pass), 128 * (i >> 2));
      }
    }
#pragma unroll 1
    for (int i = 0; i < 5; i++) {
      mbar_wait(br + 40 * pass + 8 * i, 0);
      SPROF(5 * pass + i);
      if (warp == 1 && SPF == 0) { e_pf3d(&tm.win, c0 + 32 - 32 * pass, 128 * i); e_pf3d(&tm.win, c0 + 32 - 32 * pass, 128 * i + 64); }
      if (seg < 2 || lg < 3) {
        uint4 v[4];
#pragma unroll
        for (int e = 0; e < 4; e++) v[e] = lds128(sb + i * 32768 + bx * 8192 + ((4 * e + kq) * 8 + kr) * 64 + ((ck ^ (kr >> 1)) << 4));
#pragma unroll
        for (int e = 0; e < 4; e++) stg128(p.s->ws + (((pass * 4 + cq) * 80 + 16 * i + 4 * e + kq) * 11 + seg * 4 + lg) * 64 + kr * 8, v[e]);
      }
    }
    if (warp == 1 && SPF == 1)
      for (int i = 0; i < 10; i++) e_pf3d(&tm.win, c0 + 32 - 32 * pass, 64 * i);
    release(I_WS + pass);
  }
  auto fetch = [&](int r) {
    const int c2 = (cq + r) & 3;
    e_expect(br + 96 + 8 * r, 69120);
#pragma unroll 1
    for (int e = 0; e < 9; e++) e_tma2d(sb + (r % 3) * 69120 + e * 7680, &tm.wout, br + 96 + 8 * r, 160 * cq, e < 8 ? 192 * c2 + 24 * e : 768 + 24 * c2);
  };
  if (warp == 0) { fetch(0); fetch(1); fetch(2); }
#pragma unroll 1
  for (int r = 0; r < 4; r++) {
    mbar_wait(br + 96 + 8 * r, 0);
    SPROF(13 + (r >> 1));
#pragma unroll 1
    for (int u = warp * 4 + lg; u < 135; u += 48) {
      const int gm = u / 5, be = u % 5, kg = r == 0 ? (gm < 16 ? gm + 10 : gm < 26 ? gm - 16 : 26) : gm < 16 ? 44 + 16 * r + gm : 11 * r + gm;
      const u32 a = sb + (r % 3) * 69120 + (gm * 8 + kr) * 320 + be * 64;
      const uint4 v0 = lds128(a), v1 = lds128(a + 16), v2 = lds128(a + 32), v3 = lds128(a + 48);
      u16* dst = p.s->wo + (cq * 540 + kg * 5 + be) * 256 + kr * 8;
      stg128(dst, make_uint4(v0.x, v1.x, v2.x, v3.x));
      stg128(dst + 64, make_uint4(v0.y, v1.y, v2.y, v3.y));
      stg128(dst + 128, make_uint4(v0.z, v1.z, v2.z, v3.z));
      stg128(dst + 192, make_uint4(v0.w, v1.w, v2.w, v3.w));
    }
    if (r == 0) { __syncthreads(); if (warp == 0) fetch(3); }
  }
  release(I_WO);
}

__global__ void __launch_bounds__(384, 1) mega_kernel(const __grid_constant__ Params p, const __grid_constant__ Maps tm) {
  extern __shared__ __align__(1024) unsigned char smem_raw[];
  const u32 t_start = clock();
  const int tid = threadIdx.x, warp = __shfl_sync(0xffffffffu, tid >> 5, 0), lane = tid & 31;
  int role;
  {
    u32 sm; asm volatile("mov.u32 %0, %%smid;" : "=r"(sm));
    const u32 x = sm - 64, q = (x * 4682u) >> 16;
    const u32 lo = ((sm + 14) & 14) * 8 + (sm >> 4) * 2, hi = ((x - 14 * q) & 14) * 8 + 8 + 2 * q;
    role = sm >= 124 ? sm - 4 : sm >= 120 ? sm + 8 : (sm < 64 ? lo : hi) + (sm & 1);
    role = __shfl_sync(0xffffffffu, role, 0);
  }
  if (role >= 128) { trap_if_gt(smem_u32(smem_raw) ^ sb, 0); spare_cta(p, tm, role - 128, tid, warp); return; }
  const int rt = role >> 2, cq = role & 3;

  e_init(bar(48 + warp), 2);
  if (warp == 8) {
    e_expect(bar(B_KV), KVP);
    e_tma2d(sb, &tm.k, bar(B_KV), 64 * (role & 1), 32 * (role >> 1) - 3);
    e_tma2d(sb + VO, &tm.v, bar(B_KV), 64 * (role & 1), 32 * (role >> 1));
    e_xload(sb + SHK, p.shk, 5120, bar(B_KV));
    PROF(lane == 0, 0);
  }
  if (warp < 6) e_tmpf(&tm.ssm + warp);
  e_init6(bar(warp), (u32)(0x111111a88882ull >> (4 * warp)) & 15);
  if (warp == 8) { e_expect(bar(B_SS), 4096); e_tma2d(sb + kslot(0), &tm.ssm, bar(B_SS), 0, 8 * role); PROF(lane == 0, 98); }
  if (tid < 63) {
    sts128(sb + (tid < 5 ? US + tid * UP + 4096 : tid < 15 ? kslot((tid - 5) >> 1) - 16 + (tid & 1) * KO : PWB + ((tid - 15) & 7) * PWP + ((tid - 15) >> 3) * 16), make_uint4(0, 0, 0, 0));
    fence_async_smem();
  }
  __syncthreads();

  if (warp < 8) {
    asm volatile("setmaxnreg.inc.sync.aligned.u32 224;");
    u32 dv;
    asm volatile("ld.global.nc.u16 %0, [%1];" : "=r"(dv) : "l"(p.ssmD + (tid & 128) + role));
    u32 ep = ld_rlx32(p.s->ctr);
    const int wg = warp >> 2, w = warp & 3, t128 = tid & 127, g = lane >> 2, t = lane & 3;
    const bool elect = t128 == 0;
    const u32 ts = __shfl_sync(0xffffffffu, t_start, 0);
    PROF(tid == 0, 1);
    {
      const u32 koff = sb + ((g & 1) ? 0 : KO) + 4 * (t + (g >> 1) - 3) + 32 * w;
      const u32 pw = sb + PWB + wg * 4 * PWP;
      u32 a[64];
      ep = __shfl_sync(0xffffffffu, ep, 0);
      consume(dv);
      if (wg) mbar_wait(bar(B_KV), 0);
#pragma unroll 1
      for (u32 js = wg ? RND1 : RND0; js != 15; js >>= 4) {
        const int j = js & 15;
        mbar_wait(bar(B_KV + j), 0);
        PROF(elect, j < 2 ? 2 + j : j == 2 ? 91 : j == 3 ? 126 : 93);
        phase_a<1>(p, j, w, role, lane_now(), (ep & 1) - 1);
        PROF(elect, j < 2 ? 4 + j : j == 2 ? 90 : j == 3 ? 127 : 79);
        if (j < 2) {
          mbar_wait(bar(B_SS + wg), 0);
          shift_copy<2, 2048>(sb + kslot(wg) + t128 * 16, dv, elect);
          bsync(1 + wg, 128);
          load_a<0, 16>(a, koff + kslot(wg));
          PROFD(elect, 6 + wg, a[63]);
        }
      }
#pragma unroll 1
      for (int ch = wg; ch < 5; ch += 2) {
        float d[128];
        const u32 pn = koff + kslot(ch + 2), ps = pw + w * (PWP + 32) + (255 - lane_now()) * 16, lo = desc_lo(sb + US + ch * UP, 16);
        const bool more = ch < 3;
        mbar_wait(bar(B_UV + ch), 0);
        if (ch > 0) bsync(3 + wg, 256);
        if (ch == 4) stamp_post(p.s->ctr, ep, S_Y, ts, lane_now() + w);
        PROF(elect, 8 + ch);
        wg_fence();
        conv_pair<0>(d, a, lo); conv_pair<1>(d, a, lo); conv_pair<2>(d, a, lo);
        if (R0 == 0 && more) mbar_wait(bar(B_KB + ch), 0);
        wg_wait<2>();
        mbar_arrive_if(bar(B_EMPTY) + 8 * (ch == 1 ? w >> 1 : ch - 1), w < ((H4 ? 0x12020 : 0x12040) >> (4 * ch) & 7) && lane_now() == 0);
        conv_work<0>(d, a, ps, pn, more); conv_pair<3>(d, a, lo);
        if (R0 == 1 && more) mbar_wait(bar(B_KB + ch), 0);
        wg_wait<2>(); conv_work<1>(d, a, ps, pn, more); conv_pair<4>(d, a, lo);
        if (R0 == 2 && more) mbar_wait(bar(B_KB + ch), 0);
        wg_wait<2>(); conv_work<2>(d, a, ps, pn, more); conv_pair<5>(d, a, lo); conv_pair<6>(d, a, lo); conv_pair<7>(d, a, lo);
        if (ch < 4) barrive(4 - wg, 256);
        if (R0 == 3 && more) mbar_wait(bar(B_KB + ch), 0);
        wg_wait<2>(); conv_work<3>(d, a, ps, pn, more); conv_work<4>(d, a, ps, pn, more); conv_work<5>(d, a, ps, pn, more);
        wg_wait<0>();
        PROFD(elect, 13 + ch, __float_as_uint(d[0]));
        conv_work<6>(d, a, ps, pn, more); conv_work<7>(d, a, ps, pn, more);
        bsync(1 + wg, 128);
        u32 q[2][4][4];
        const int t128 = 32 * w + lane_now();
#pragma unroll
        for (int h = 0; h < 2; h++)
#pragma unroll
          for (int i = 0; i < 4; i++) lds128(q[h][i], pw + i * PWP + h * 2048 + t128 * 16);
        if (more) load_a<16 - 2 * R0, 16>(a, pn);
        u16* yp = p.s->y + ((t128 >> 3) * 640 + 128 * ch + role) * 64 + ((t128 & 7) << 3);
#pragma unroll
        for (int h = 0; h < 2; h++) {
          u32 y[4];
#pragma unroll
          for (int e = 0; e < 4; e++) y[e] = hadd2(hadd2(q[h][0][e], q[h][1][e]), hadd2(q[h][2][e], q[h][3][e]));
          stg128(yp + h * (16 * 640 * 64), make_uint4(tagw(y[0], ~t128 & 1, ~ep), y[1], y[2], y[3]));
        }
        PROF(elect, 18 + ch);
      }
    }
    u32 zp[32], x1[5][4];
    u32* hp = (u32*)p.s->h2 + ((rt * 80 + 2 * warp) * 8 + 2 * cq) * 32 + lane;
    {
      u32 x[5][4], S[5][2], C[5][2], r2[2], n2[2];
      float c[3][4];
      const u32 xa = sb + QS + wg * 2048 + (lane & 15) * 128 + (((2 * w + (lane >> 4)) ^ (lane & 7)) << 4);
      const u32 ya = sb + YS + (16 * warp + (lane >> 4) * 8 + (lane & 7)) * 32 + ((((lane >> 3) ^ (lane >> 2)) & 1) << 4);
      const u32 ma = sb + M_MOD + 64 * (warp >> 1) + 16 * t + 8 * (warp & 1), la = sb + M_LN + g * 16, par = (ep & 1) - 1;
      auto clear = [&]() {
#pragma unroll
        for (int i = 0; i < 12; i++) c[i >> 2][i & 3] = 0.f;
      };
      mbar_wait(bar(B_Q), 0);
      PK(elect, 23 + wg);
#pragma unroll
      for (int j = 0; j < 5; j++) ldsm4(x[j], xa + j * 4096);
      if (wg) asm volatile("st.global.v2.b32 [%0], {%1,%1};" ::"l"(p.s->stz + role * 128 + t128), "r"(ep) : "memory");
      if (wg) {
        clear();
#pragma unroll
        for (int j = 0; j < 5; j++) ldsm4(x1[j], xa + j * 4096 - 2048);
#pragma unroll
        for (int j = 0; j < 5; j++) { row_stats(c, x[j]); row_stats(c, x1[j]); }
        ln_post(c, la + w * 128, lane);
        bsync(2, 128);
        ln_params<4>(la, r2, n2);
        if (w == 0) sts128(la + 512, make_uint4(r2[0], r2[1], n2[0], n2[1]));
        barrive(5, 256);
      } else {
        bsync(5, 256);
        const uint4 v = lds128(la + 512);
        r2[0] = v.x; r2[1] = v.y; n2[0] = v.z; n2[1] = v.w;
      }
      u32 xn[5][4];
#pragma unroll
      for (int i = 0; i < 20; i++) xn[i >> 2][i & 3] = opaque(hfma2(x[i >> 2][i & 3], r2[i & 1], n2[i & 1]));
      PROFD(elect, 25 + wg, r2[0]);
#pragma unroll 1
      for (u32 ph = 0;; ph++) {
        u32 T[5][4], m = 1, bad = 0;
        mbar_wait(bar(B_YF + 2), ph & 1);
        PROF(elect && wg == 0 && ph == 0, 88);
#pragma unroll
        for (int j = 0; j < 5; j++) {
          u32 A[2], B[2], G[2];
          lds64(B, ma + j * 256); lds64(A, ma + j * 256 + 1280); lds64(G, ma + j * 256 + 2560); lds64(S[j], ma + j * 256 + 3840); lds64(C[j], ma + j * 256 + 5120);
#pragma unroll
          for (int i = 0; i < 2; i++) {
            m = min(min(min(m, A[i]), min(B[i], G[i])), min(S[j][i], C[j][i]));
            A[i] = hmul2(G[i], hadd2(A[i], ONE2)); B[i] = hmul2(G[i], B[i]); C[j][i] = hadd2(C[j][i], ONE2);
          }
#pragma unroll
          for (int i = 0; i < 4; i++) T[j][i] = hfma2(xn[j][i], A[i >> 1], B[i >> 1]);
        }
        clear();
#pragma unroll
        for (int j = 0; j < 5; j++) {
          u32 y[4];
          if (j == YG) PROFD(elect && ph == 0, 27 + wg, __float_as_uint(c[2][0]));
          if (j == 0 || j == YG) mbar_wait(bar(B_YF + (j > 0)), ph & 1);
          if (j == YG) tile_post(p.s->ctr + 32 + 32 * rt + cq, ts, ep, tid == 0);
          if (j == 0 || j == YG) PROF(elect && wg == 0 && ph == 0, j ? 92 : 89);
          ldsm4t(y, ya + j * 4096);
          bad |= (y[0] ^ par) | (y[2] ^ par);
#pragma unroll
          for (int i = 0; i < 4; i++) x1[j][i] = hfma2(y[i], T[j][i], x[j][i]);
          row_stats(c, x1[j]);
        }
        ln_post(c, la + 1024 + warp * 128, lane);
        PROFV(elect, 96, 100 * ph + 100);
        if (__all_sync(0xffffffffu, bsync_and(7, 256, m != 0 && (g != 0 || (bad & 0x10001) == 0)))) break;
        trap_if_gt(ph, 1 << 16);
        RST(__any_sync(0xffffffffu, m == 0) ? 1 : __any_sync(0xffffffffu, g == 0 && (bad & 0x10001)) ? 2 : 0);
        if (warp == 0) { fetch_y(tm, 0, YG, role); fetch_y(tm, YG, 5, role); e_xload(sb + M_MOD, p.s->mod, 6400, bar(B_YF + 2)); }
      }
      mbar_arrive_if(bar(B_HD), lane == 0);
      const u32 th = clock();
      ln_params<8>(la + 1024, r2, n2);
      PROFD(elect, 29 + wg, r2[0]);
      const u32 m0 = (lane & 7) == 2 * cq, m1 = (lane & 7) == 2 * cq + 1;
#pragma unroll
      for (int j = 0; j < 5; j++) {
#pragma unroll
        for (int i = 0; i < 4; i++) {
          const u32 hv = tagw(hfma2(hfma2(x1[j][i], r2[i & 1], n2[i & 1]), C[j][i >> 1], S[j][i >> 1]), (i & 1) ? m1 : m0, par);
          if (j < NH) stg32(hp + (16 * j + (i >> 1)) * 256 + (i & 1) * 32, hv); else zp[4 * j + i] = hv;
        }
        if (j < NH - 1) { until(th, G_S0 + j * G_S); __syncwarp(); }
      }
      PK(elect, 31 + wg);
    }
    const int vg = wg ^ SWAPWG;
    float z[64];
    u32* z2p = (u32*)p.s->z2 + (role * 8 + 2 * w) * 27 * 32 + lane;
#pragma unroll 1
    for (int pass = 0; pass < 2; pass++) {
      if (vg == 0) g1_pass<128>(z, zp, x1[0], pass, t128, z2p, hp, ep);
      else g1_pass<88>(z, zp, x1[0], pass, t128, z2p, hp, ep);
      float st[4] = {0.f, 0.f, 0.f, 0.f};
      auto act = [&](int n0, int n1) {
#pragma unroll
        for (int i = 2 * n0; i < 2 * n1; i++) {
          const float u0 = gelu2(z[2 * i]), u1 = gelu2(z[2 * i + 1]);
          zp[i] = pack2(u0, u1);
          st[2 * (i & 1)] += u0 + u1; st[2 * (i & 1) + 1] = fmaf(u1, u1, fmaf(u0, u0, st[2 * (i & 1) + 1]));
        }
      };
      act(0, 11);
      if (vg == 0) act(11, 16);
      if (pass == 0) {
        const bool up = t & 2;
        float a = (up ? st[2] : st[0]) + shx(up ? st[0] : st[2], 2), q = (up ? st[3] : st[1]) + shx(up ? st[1] : st[3], 2);
        a += shx(a, 1); q += shx(q, 1);
        if (!(t & 1))
          asm volatile("st.relaxed.gpu.global.v2.b32 [%0], {%1,%2};" ::"l"(p.s->stz + (role * 64 + 16 * w + g + 4 * t) * 2 + vg), "f"(a), "r"(prmt(__float_as_uint(q), ep + 1, 0x3214)) : "memory");
        __syncwarp();
        mbar_arrive_if(bar(B_ZP), lane == 0);
      }
      PROFD(elect, 113 + 2 * pass + vg, zp[21]);
    }
    const u32 bs0 = lds32(sb + M_BS + (16 * w + g) * 4), bs1 = lds32(sb + M_BS + (16 * w + g + 8) * 4);
    if (vg == 0) g2_pass<128>(z, elect); else g2_pass<88>(z, elect);
    PROFD(elect, 45 + vg, __float_as_uint(z[0]));
    {
      u32* Pp = (u32*)p.s->P + ((role * 27 + 16 * vg) * 8 + 2 * w) * 32 + lane;
      const u32 m0 = (lane & 7) == 2 * w, m1 = (lane & 7) == 2 * w + 1;
      auto put = [&](int n) { stg32(Pp + n * 256, zp[2 * n]); stg32(Pp + n * 256 + 32, zp[2 * n + 1]); };
      auto gate = [&](int n0, int n1) {
#pragma unroll
        for (int n = n0; n < n1; n++) {
          zp[2 * n] = tagw(hmul2(zp[2 * n], hfma2(pack2(z[4 * n], z[4 * n + 1]), 0x3f003f00u, bs0)), m0, ~ep);
          zp[2 * n + 1] = tagw(hmul2(zp[2 * n + 1], hfma2(pack2(z[4 * n + 2], z[4 * n + 3]), 0x3f003f00u, bs1)), m1, ~ep);
          if (n < NPE) put(n);
        }
      };
      gate(0, 11);
      if (vg == 0) {
        mbar_arrive_if(bar(B_PD), lane == 0);
        gate(11, 16);
#pragma unroll
        for (int n = 0; n < 16; n += 2) stsm4(sb + (((lane >> 4) + n) * 8 + 2 * w) * 128 + (lane & 15) * 16, zp + 2 * n);
        fence_async_smem();
        barrive(5, 256);
      }
#pragma unroll
      for (int n = NPE; n < 11; n++) put(n);
      if (vg == 0) {
#pragma unroll
        for (int n = 11; n < 16; n++) put(n);
      }
    }
    if (vg) {
      float o[80];
      u32 res[60], all = 0;
      PK(elect, 120);
      mbar_wait(bar(B_RES), 0);
      const u32 ra = sb + (t * 8 + 2 * w) * 128 + (g ^ (2 * t)) * 16;
      auto get = [&](int e0, int e1) {
#pragma unroll
        for (int e = e0; e < e1; e++) lds128(res + 4 * e, e < 10 ? ra + (e < 6 ? RES + (e >> 1) * 4096 : e < 8 ? M_MOD : RES2) + (e & 1) * 128 : sb + RES2 + 4096 + (e - 10) * 64 + t * 16);
      };
      get(0, NR0);
      mbar_wait(bar(B_WF), 0); mbar_wait(bar(B_WF + 1), 0);
      bsync(4, 256);
      PROF(elect, 50);
      wg_fence();
#pragma unroll
      for (int q = 0; q < 5; q++) { wgmma_rs_160(o, zp + 4 * q, desc_join(desc_lo(sb + BT + q * 5120, 2560), 8u), q); if (q == 2 || q == 4) wg_commit(); }
      stsm2(sb + XR + 2 * w * 128 + (lane & 15) * 16, zp[20], zp[21]);
      fence_async_smem();
      get(NR0, NR1);
      bsync(5, 256);
      PK(elect, 48);
      wg_fence();
      wgmma_ss_160(o, desc_join(desc_lo(sb, 1024), 8u), desc_join(desc_lo(sb + BT + 5 * 5120, 2560), 8u), 1);
      wg_commit();
      wg_wait<1>();
      mbar_arrive_if(bar(B_WE), elect);
      u32 la = desc_lo(sb + 2048, 1024), lb = desc_lo(sb + BT + 2 * WOST, 2560), bf = bar(B_WF + 2), bprev = bar(B_WE + 1), par = 0, bv = bar(B_PV - 1), kb = 4;
#pragma unroll 1
      do {
        bool go;
        if (kb == 16) {
          get(NR1, 15);
#pragma unroll
          for (int e = 0; e < 15; e++) all ^= res[4 * e];
          consume(all);
          mbar_arrive_if(bar(B_PD), lane == 0);
        }
        if (kb >= 16) mbar_wait(bv, 0);
        mbar_wait(bf, par);
        PROF(elect && kb == 16, 49);
#pragma unroll 1
        do {
          wg_fence();
          wgmma_ss_160(o, desc_join(la, 8u), desc_join(lb, 8u), 1);
          la += kb == 16 ? (XR >> 4) - 7 * 128 : 128;
          const u32 bcur = bf + 8 * (B_WE - B_WF);
          const bool wrap = kb & 0x2040;
          kb *= 2; par ^= wrap; bf += wrap ? -48 : 8; bv += (kb & 0x9550) ? 8 : 0;
          const bool t0 = mbar_test(bf, par), t1 = mbar_test(bv, 0);
          wgmma_ss_160(o, desc_join(la, 8u), desc_join(lb + 320, 8u), 1);
          wgmma_ss_160(o, desc_join(la + 128, 8u), desc_join(lb + 640, 8u), 1);
          wg_commit();
          go = __all_sync(0xffffffffu, t0 & (t1 | (kb < 16)) & !(kb & 0x40010));
          la += 256; lb += wrap ? -6 * (int)(WOST >> 4) : (int)(WOST >> 4);
          wg_wait<1>();
          mbar_arrive_if(bprev, elect);
          bprev = bcur;
          PROFG(elect, 33 - __clz(kb));
        } while (go);
      } while (kb != 0x40000);
      wg_wait<0>();
      PROFD(elect, 52, __float_as_uint(o[0]));
      u16* op = p.out + (rt * 64 + 16 * w + g) * 640 + 160 * cq + 8 * t;
#pragma unroll
      for (int i = 0; i < 10; i++) {
        const int be = i >> 1, h = i & 1;
        u32 r[4];
#pragma unroll
        for (int e = 0; e < 4; e++) r[e] = hfma2(pack2(o[16 * be + 4 * e + 2 * h], o[16 * be + 4 * e + 2 * h + 1]), res[40 + 4 * be + e], res[4 * i + e]);
        stg128(op + h * 8 * 640 + 32 * be, make_uint4(r[0], r[1], r[2], r[3]));
      }
      PK(elect, 53);
    }
  } else {
    asm volatile("setmaxnreg.dec.sync.aligned.u32 56;");
    const int hw = warp - 8;
    if (hw == 0) {
      {
        const int n = lane < 15 ? (int)(ORDER >> (4 * lane)) & 15 : lane, j = n < 15 ? (n * 11) >> 5 : n < 20 ? n - 15 : n - 20, ty = n < 15 ? n - 3 * j : n < 20 ? 3 : 4;
        const int c0 = ty < 2 ? 128 * j + 64 * (role & 1) : ty == 2 ? 0 : ty == 3 ? 32 * role : 64 * j;
        const int c1 = ty < 2 ? 32 * (role >> 1) - 3 + 3 * ty : ty == 2 ? 1024 * j + 8 * role : ty == 3 ? 128 * j : 16 * role;
        const u32 dst = sb + (ty < 2 ? j * KVP + ty * VO : ty == 2 ? kslot(j) : ty == 3 ? WM + j * 8192 : QS + j * 2048);
        const u32 br = bar(ty < 2 ? B_KV + j : ty == 2 ? B_SS + j : ty == 3 ? B_WM + j : B_Q), bytes = ty == 0 ? VO : ty < 3 ? 4096 : ty == 3 ? 8192 : 2048;
        int due = T_0 + 3 * T_G;
#pragma unroll 1
        for (int i = 3; i < 30; i++) {
          until(t_start, due);
          if (lane == i) xtma2d(dst, &tm.k + ty, br, c0, c1, bytes);
          PROF(lane == i && (i < 4 || i == 29), 96 + lane);
          due += i < 15 ? T_G + (i == 14 ? T_X : 0) : i < 20 ? 2 * T_G2 : T_G2 / 2;
          __syncwarp();
        }
      }
      const u32 ep = ld_rlx32(p.s->ctr);
      {
        ctr_poll(p.s->ctr, I_WS, ep, 4);
        PROF(lane == 0, 33);
        const u16* src = p.s->ws + cq * 56320;
#pragma unroll 1
        for (int r = 0; r < 4; r++) {
          if (r == 2) { mbar_wait(bar(B_WS1), 0); if (WL < 5) mbar_wait(bar(B_EMPTY + WL), 0); else mbar_wait(bar(B_FULL + 4), 1); src += 3 * 56320; }
#pragma unroll 1
          for (int s = 0; s < 5; s++, src += 5632) {
            if (r == 0) until(t_start, T_W + s * G_W);
            w_g1(bar(B_EMPTY) + 8 * s, r & 1, bar(B_FULL) + 8 * s, sb + s * BT, &tm.win, (r < 2 ? 896 : 0) + 192 * cq, 64 * s + 320 * (r & 1), src);
            PROF(lane == 0 && r == 0, 74 + s); PROFG(lane == 0 && r == 2 * PG1 + 1, 21 + s);
          }
        }
      }
      e_expect(bar(B_FULL + 5), BT + 8192);
      e_tma2d(sb + AR, &tm.wsp, bar(B_FULL + 5), 0, 64 * rt);
      mbar_wait(bar(B_Z2D), 0);
      const int tz = lds32(sb + M_TZ);
      fence_gpu();
      ctr_arrive(p.s->ctr, I_Z2, ep, lane);
      PROF(lane == 0, 36);
      until(t_start, tz + D_Z);
      PROF(lane == 0, 35);
      {
        const u16* src = p.s->z2 + cq * (BT / 2);
        u32 par = 0;
#pragma unroll 1
        for (int c0 = 0;; par ^= 1) {
#pragma unroll
          for (int e = 0; e < 6; e++, c0 += 64, src += 2 * BT) {
            const int s = (e + 5) % 6;
            if (e == 2 && c0 == 2048) break;
            if (e == 0 && c0 == 0) e_load(sb + s * BT, src, BT, bar(B_FULL + s)); else
            w_g2(bar(B_EMPTY + s), e ? par : par ^ 1, bar(B_FULL + s), sb + s * BT, src, sb + AR + e * 8192, &tm.wsp, c0, 64 * rt);
            if (e == NV - 1 && c0 < 384) { ctr_poll(p.s->ctr, I_Z2, ep, 128); PROF(lane == 0, 37); }
          }
          if (c0 == 2048) break;
          if (c0 == 1152) {
            e_expect(bar(B_RES), 20800);
            e_load(sb + M_MOD, p.s->x1 + role * 10240 + 6144, 4096, bar(B_RES));
            e_load(sb + RES2, p.s->x1 + role * 10240 + 8192, 4096, bar(B_RES));
            e_load(sb + RES2 + 4096, p.s->mod + 3200 + 160 * cq, 320, bar(B_RES));
          }
        }
      }
      if (role == 0 && lane < 9) p.s->ctr[lane ? 15 - 8 * (ep & 1) + lane : 0] = lane ? 0 : ep + 1;
      if (role < 100 && lane < 16) stg32((u32*)p.s->mod + role * 16 + lane, 0);
      mbar_wait(bar(B_WO), 0);
      {
        const u16* src = p.s->wo + cq * 18 * (WOST / 2);
#pragma unroll 1
        for (int i = 0; i < 7; i++, src += WOST / 2) {
          w_load<WOST>(bar(B_EMPTY + 1) + 8 * ((i + 1) >> 1), 1, bar(B_WF) + 8 * i, sb + BT + i * WOST, src);
          stamp_post(p.s->ctr, ep, S_P, t_start, lane + i);
          if (i == 2) e_load(sb + RES, p.s->x1 + role * 10240, 12288, bar(B_RES));
        }
        int due = stamp_wait(p.s->ctr, ep, S_P) + T_R;
#pragma unroll 1
        for (int r = 0; r < 2; r++) {
#pragma unroll 1
          for (int i = 0; i < 7 - 3 * r; i++, src += WOST / 2, due += G_R) { until(t_start, due); w_load<WOST>(bar(B_WE) + 8 * i, r, bar(B_WF) + 8 * i, sb + BT + i * WOST, src); }
        }
      }
    } else {
      u32 rph = 0, ep = ld_rlx32(p.s->ctr);
      if (hw == 1) {
        tile_wait(p.s->ctr + 32 + 32 * rt, ep - 1);
#pragma unroll 1
        for (int j = 0; j < 5; j++) {
          const int due = j ? T_U1 + j * T_UP : T_U0;
          until(t_start, due - D_U);
          if (!__all_sync(0xffffffffu, mbar_test(bar(B_KV + j), 0))) { mbar_wait(bar(B_KV + j), 0); until(clock(), D_U); }
          until(t_start, due);
          PROF(lane == 0, j ? 53 + j : 38);
          const u16* src = p.s->u + (128 * j + role) * 2048;
          e_xload(sb + US + j * UP, src, 4096, bar(B_RF));
          rph ^= 1;
          const int n = validate<4>(bar(B_RF), rph ^ 1, sb + US + j * UP, lane * 32, ep, bar(B_UV + j), src, bar(B_RF), rph);
          if (n) RST(j ? j > 1 ? 3 + j : 3 : 10);
          PROF(lane == 0, 64 + j); PROFV(lane == 0, 69 + j, 100 * n + 100);
        }
        mbar_wait(bar(B_EMPTY + 3), 0);
        const int ty = stamp_wait(p.s->ctr, ep, S_Y);
        if (YG == 4) until(t_start, ty + D_Y3);
        fetch_y(tm, 0, YG, role);
        PROF(lane == 0, 58);
        until(t_start, ty + D_Y);
        fetch_y(tm, YG, 5, role);
        PROF(lane == 0, 59);
        {
          mbar_wait(bar(B_YF + 1), 0);
          const u32 t0 = t_start + max(tile_wait(p.s->ctr + 32 + 32 * rt, ep), ty + D_Y + D_HG);
          mbar_wait(bar(B_HD), 0);
#pragma unroll 1
          for (int j = 0; j < 5; j++) {
            until(t0, D_H + j * G_H);
            e_xload(sb + XR + j * 16384, p.s->h2 + (rt * 5 + j) * 8192, 16384, bar(B_SS + j));
            PROF(lane == 0 && j == 0, 60);
          }
        }
        const u32 t0 = clock();
#pragma unroll 1
        for (int i = 0; i < 16; i++) { until(t0, i * T_PF); e_prefetch(p.wsp + (role * 16 + i) * 2048, 4096); }
      } else {
        const int hi = hw - 2;
        const u32 ts = __shfl_sync(0xffffffffu, t_start, 0);
        const u32 d0 = __ldg(p.ssmD + 128 * min(lane, 4) + role);
        {
          const int ht = tid - 320, g = lane >> 2, t = lane & 3;
          const u32 bs = __ldg(p.bsp + rt * 64 + ht);
          u32 cv[5];
#pragma unroll
          for (int i = 0; i < 5; i++) cv[i] = __ldg((const u32*)p.c + ht + 64 * i);
#pragma unroll 1
          for (int i = 0; i < 5; i++) {
            const float a = bflo(cv[0]), b = bfhi(cv[0]);
            const u32 v = pack2(__fdividef(a, 1.f + __expf(-a)), __fdividef(b, 1.f + __expf(-b))), ad = sb + M_SC + i * 256 + hi * 128 + t * 32 + g * 2;
            sts16(ad, v); sts16(ad + 16, v >> 16);
#pragma unroll
            for (int j = 0; j < 4; j++) cv[j] = cv[j + 1];
          }
          sts32(sb + M_D + 4 * min(lane, 4), d0);
          sts32(sb + M_BS + 4 * ht, hmul2(bs * 0x10001u, 0x3f003f00u));
          __syncwarp();
        }
        ep = __shfl_sync(0xffffffffu, ep, 0);
        mbar_wait(bar(B_KV), 0);
#pragma unroll 1
        for (int j = 2; j < 5; j++) {
          const int lane = lane_now(), ht = 32 * hi + lane;
          if (H4 && j == 4) {
            mbar_wait(bar(B_KV + 4), 0);
            PROF(ht == 0, 93);
            phase_a<2>(p, 4, hi, role, lane, (opaque(ep) & 1) - 1);
            __syncwarp();
            e_arrive(bar(B_EMPTY + 1));
            PROF(ht == 0, 79);
          }
          mbar_wait(bar(B_SS + j), 0);
          shift_copy<4, 1024>(sb + kslot(j) + hi * 512 + lane_now() * 16, lds32(sb + M_D + 4 * j), hi + lane_now() == 0);
          __syncwarp();
          e_arrive(bar(B_KB + j - 2));
          PROF(ht == 0, 78 + j);
        }
        const int lane = lane_now(), ht = 32 * hi + lane, g = lane >> 2;
        {
          float acc[8] = {0.f, 0.f, 0.f, 0.f, 0.f, 0.f, 0.f, 0.f};
#pragma unroll 1
          for (int j = 0; j < 5; j++) {
            u32 cv[4], wv[8][4];
            mbar_wait(bar(B_WM + j), 0);
            if (j == 4) stamp_post(p.s->ctr, ep, S_MOD, ts, ht);
            PROF(ht == 0, 83 + j);
            lds128(cv, sb + M_SC + j * 256 + hi * 128 + g * 16);
#pragma unroll
            for (int i = 0; i < 8; i++) lds128(wv[i], sb + WM + j * 8192 + hi * 4096 + i * 512 + lane * 16);
#pragma unroll
            for (int i = 0; i < 8; i++) {
              const float c = (i & 1) ? bfhi(cv[i >> 1]) : bflo(cv[i >> 1]);
#pragma unroll
              for (int e = 0; e < 4; e++) { acc[2 * e] = fmaf(bflo(wv[i][e]), c, acc[2 * e]); acc[2 * e + 1] = fmaf(bfhi(wv[i][e]), c, acc[2 * e + 1]); }
            }
          }
          const u32 pa = sb + WM + hi * 4096;
          sts128(pa + lane * 32, make_uint4(__float_as_uint(acc[0]), __float_as_uint(acc[1]), __float_as_uint(acc[2]), __float_as_uint(acc[3])));
          sts128(pa + lane * 32 + 16, make_uint4(__float_as_uint(acc[4]), __float_as_uint(acc[5]), __float_as_uint(acc[6]), __float_as_uint(acc[7])));
          bsync(6, 64);
          if (ht < 16) {
            float s[4] = {0.f, 0.f, 0.f, 0.f};
            const u32 ra = sb + WM + (role < 100 ? (ht & 3) * 32 + (ht >> 2) * 8 : ht * 8);
#pragma unroll
            for (int i = 0; i < 16; i++) { u32 v[2]; lds64(v, ra + (i >> 3) * 4096 + (i & 7) * 128); s[i & 2] += __uint_as_float(v[0]); s[(i & 2) + 1] += __uint_as_float(v[1]); }
            stg32((u32*)p.s->mod + role * 16 + ht, nz(pack2(s[0] + s[2], s[1] + s[3])));
          }
          __syncwarp();
          mbar_arrive_if(bar(B_EMPTY + 3), ht == 0);
          PROF(ht == 0, 39);
        }
        if (hi == 0) {
          until(ts, stamp_wait(p.s->ctr, ep, S_MOD) + D_M);
          PROF(lane == 0, 95);
          e_xload(sb + M_MOD, p.s->mod, 6400, bar(B_YF + 2));
        }
#pragma unroll 1
        for (int i = 0; i < 5; i++) {
          const int n = validate<8>(bar(B_SS + i), 1, sb + XR + i * 16384 + hi * 8192, lane * 32 + g * 4, ep, bar(B_VAL + i),
                                    p.s->h2 + (rt * 5 + i) * 8192 + hi * 4096, bar(B_RF + hw - 1), rph);
          if (i == 0) { e_arrive(bar(B_EMPTY + 4)); stamp_post(p.s->ctr, ep, S_Z, ts, ht); }
          if (i == 1 && hi == 0) { ctr_poll(p.s->ctr, I_WS + 1, ep, 4); e_arrive(bar(B_WS1)); PROF(lane == 0, 34); }
          PROF(ht == 0 && (i == 0 || i == 4), i ? 63 : 62); PROFV(ht == 0 && n, 97, 100 * i + 100);
        }
        if (hi) sts32(sb + M_TZ, stamp_wait(p.s->ctr, ep, S_Z));
        {
          mbar_wait(bar(B_ZP), 0);
          until(clock(), T_ZS);
          float s, q;
          int n = 0;
#pragma unroll 1
          while (true) {
            uint4 v[4];
            u32 bad = 0;
#pragma unroll
            for (int i = 0; i < 4; i++) v[i] = ld_rlx128(p.s->stz + ((rt * 4 + i) * 64 + ht) * 2);
            s = 0.f; q = 0.f;
#pragma unroll
            for (int i = 0; i < 4; i++) {
              bad |= (v[i].y ^ (ep + 1)) | (v[i].w ^ (ep + 1));
              s += __uint_as_float(v[i].x) + __uint_as_float(v[i].z); q += __uint_as_float(v[i].y) + __uint_as_float(v[i].w);
            }
            if (__all_sync(0xffffffffu, (bad & 255) == 0)) break;
            trap_if_gt(++n, 1 << 20);
          }
          const float mu = s * (1.f / 864.f), rs = rsq(fmaxf(q * (1.f / 864.f) - mu * mu, 0.f) + 4e-5f);
          sts32(sb + M_ZS + ht * 4, pack2(rs, -mu * rs));
          __syncwarp();
          e_arrive(bar(B_ZS));
        }
      }
      const u32 off = lane_now() * 33 & ~3;
#pragma unroll 1
      for (int i = 0, s = 5; i < NV; i++) {
        const int n = validate<9>(bar(B_FULL) + 8 * s, 0, sb + s * BT + (hw - 1) * 9216, off, ep, bar(B_ZV) + 8 * i,
                                  p.s->z2 + (i * 4 + cq) * (BT / 2) + (hw - 1) * 4608, bar(B_RF + hw - 1), rph);
        PROFV(lane == 0 && n, 118, 100 * i + 100);
        s = s == 5 ? 0 : s + 1;
      }
      if (hw == 1) { until(clock(), T_WO); ctr_poll(p.s->ctr, I_WO, ep, 4); e_arrive(bar(B_WO)); PROF(lane == 0, 94); }
      mbar_wait(bar(B_WF), 0);
      const int tp = stamp_wait(p.s->ctr, ep, S_P);
      mbar_wait(bar(B_EMPTY + 5), 1);
      const u16* src = p.s->P + (rt * 4 + ((cq + hw) & 3)) * (BT / 2);
      const u32 due = t_start + tp + ((cq + hw) & 3) * G_P, rb = bar(B_RF + hw - 1), da = sb + XR + 1024 + (hw - 1) * 11264, db = sb + XR + 34816 + (hw - 1) * 16384;
      until(due, T_P);
      e_xload(da, src + 8192, 11264, rb);
      PROF(hw == 1 && lane == 0, 100);
      rph ^= 1;
      validate<11>(rb, rph ^ 1, da, off, ep, bar(B_PV + hw - 1), src + 8192, rb, rph);
      PROF(hw == 1 && lane == 0, 101);
      until(due, T_P2);
      w_load<16384>(bar(B_PD), 0, rb, db, src);
      PROF(hw == 1 && lane == 0, 102);
      rph ^= 1;
      validate<16>(rb, rph ^ 1, db, off, ep, bar(B_PV + hw + 2), src, rb, rph);
      PROF(hw == 1 && lane == 0, 103);
    }
  }
}

typedef CUresult (*EncodeFn)(CUtensorMap*, CUtensorMapDataType, cuuint32_t, void*, const cuuint64_t*, const cuuint64_t*, const cuuint32_t*,
                             const cuuint32_t*, CUtensorMapInterleave, CUtensorMapSwizzle, CUtensorMapL2promotion, CUtensorMapFloatOOBfill);

extern "C" void kernel_launch(void* const* d_in, const int* in_sizes, int n_in, void* d_out, int out_size) {
  static EncodeFn enc = nullptr;
  if (!enc) {
    void* fn = nullptr; cudaDriverEntryPointQueryResult st;
    cudaGetDriverEntryPoint("cuTensorMapEncodeTiled", &fn, cudaEnableDefault, &st);
    enc = (EncodeFn)fn;
    cudaFuncSetAttribute(mega_kernel, cudaFuncAttributeMaxDynamicSharedMemorySize, SMEM_BYTES);
  }
  Params p;
  p.shk = (const u16*)d_in[3]; p.ssmD = (const u16*)d_in[5];
  p.wsp = (const u16*)d_in[8]; p.bsp = (const u16*)d_in[9]; p.c = (const u16*)d_in[11];
  p.out = (u16*)d_out;
  cudaGetSymbolAddress((void**)&p.s, g_s);
  auto mk = [&](void* base, int rank, cuuint64_t d0, cuuint64_t d1, cuuint32_t b0, cuuint32_t b1, CUtensorMapSwizzle sw) {
    CUtensorMap m;
    cuuint64_t gd[3] = {d0, d1, 2}, gs[2] = {d0 * 2, 128};
    cuuint32_t bd[3] = {b0, b1, 2}, es[3] = {1, 1, 1};
    enc(&m, CU_TENSOR_MAP_DATA_TYPE_BFLOAT16, rank, base, gd, gs, bd, es, CU_TENSOR_MAP_INTERLEAVE_NONE, sw, (CUtensorMapL2promotion)PROMO,
        CU_TENSOR_MAP_FLOAT_OOB_FILL_NONE);
    return m;
  };
  Maps tm;
  tm.k = mk(d_in[1], 2, 640, 2048, 64, 35, CU_TENSOR_MAP_SWIZZLE_NONE);
  tm.v = mk(d_in[2], 2, 640, 2048, 64, 32, CU_TENSOR_MAP_SWIZZLE_NONE);
  tm.ssm = mk(d_in[4], 2, 256, 5120, 256, 8, CU_TENSOR_MAP_SWIZZLE_NONE);
  tm.wmod = mk(d_in[12], 2, 3840, 640, 32, 128, CU_TENSOR_MAP_SWIZZLE_NONE);
  tm.q = mk(d_in[0], 2, 640, 2048, 64, 16, CU_TENSOR_MAP_SWIZZLE_128B);
  tm.win = mk(d_in[7], 3, 1728, 640, 64, 64, CU_TENSOR_MAP_SWIZZLE_128B);
  tm.wsp = mk(d_in[8], 2, 2048, 2048, 64, 64, CU_TENSOR_MAP_SWIZZLE_128B);
  tm.y = mk(p.s->y, 2, 64, 20480, 16, 128, CU_TENSOR_MAP_SWIZZLE_32B);
  tm.win32 = mk(d_in[7], 2, 1728, 640, 32, 128, CU_TENSOR_MAP_SWIZZLE_64B);
  tm.wout = mk(d_in[10], 2, 640, 864, 160, 24, CU_TENSOR_MAP_SWIZZLE_NONE);
  mega_kernel<<<132, 384, SMEM_BYTES>>>(p, tm);
}
```

```cpp
#include <cuda_runtime.h>
#include <cuda.h>
#include <cuda_bf16.h>
#include <stdint.h>

typedef uint16_t u16; typedef uint32_t u32; typedef unsigned long long u64;
#define DEV __device__ __forceinline__

struct Scratch {
  u32 ctr[1280];
  u16 mod[4096];
  u64 stz[128 * 64 * 2];
  u16 u[640 * 2048];
  u16 y[32 * 640 * 64];
  u16 h2[32 * 80 * 8 * 64];
  u16 x1[32 * 80 * 8 * 64];
  u16 ws[2 * 4 * 80 * 11 * 64];
  u16 wo[4 * 108 * 20 * 64];
  u16 z2[32 * 4 * 8 * 27 * 64];
  u16 P[32 * 4 * 27 * 8 * 64];
};
__device__ __align__(1024) Scratch g_s;
enum { I_WS = 0, I_WO = 2, I_Z2 = 3 };
enum { S_Y = 0, S_MOD = 1, S_Z = 2, S_P = 3 };

struct Maps { CUtensorMap k, v, ssm, wmod, q, win, wsp, y, win32, wout; };
struct Params {
  Scratch* s;
  const u16 *shk, *ssmD, *c, *wsp, *bsp;
  u16* out;
};

constexpr u32 sb = 1024;
constexpr u32 BT = 27648, XR = 5 * BT, AR = 6 * BT, MISC = XR + 81920, SMEM_BYTES = 232448;
constexpr u32 M_LN = MISC, M_BAR = MISC + 2048, M_MOD = M_BAR + 1024, M_ZS = M_MOD + 7680, M_SM = M_ZS + 256, M_PROF = M_SM + 256;
constexpr u32 M_SC = M_MOD, M_TZ = M_SM, M_D = M_SM + 16, M_BS = M_PROF + 512;
constexpr u32 US = XR, UP = 4224, PWB = US + 5 * UP, PWP = 4192, YR = 2 * BT, KP = 8320, KO = 4144, WM = YR + 41984;
constexpr u32 KVP = 8576, VO = 4480, SHK = 5 * KVP, YS = XR - 20480, QS = XR + 55296, WOST = 15360, RES = AR + 16384, RES2 = AR + 49152;
DEV u32 kslot(int j) { return YR + 128 + j * KP; }
enum { B_WM = 0, B_RF = 5, B_SS = 8, B_PV = 13, B_YF = 19, B_RES = 22, B_FULL = 23, B_WO = 29, B_WS1 = 30, B_WF = 33, B_WE = 40,
       B_VAL = 48, B_KB = 53, B_KV = 56, B_EMPTY = 61, B_ZS = 71,
       B_DUMMY = 72, B_HD = 73, B_ZP = 74, B_PD = 75, B_Z2D = 76, B_Q = 77, B_UV = 78,
       B_ZV = 84 };
DEV constexpr u32 bar(int i) { return sb + M_BAR + 8 * i; }

#define RST(i)
#define PK(cond, i)
#define PROF(cond, i)
#define PROFD(cond, i, dep)
#define PROFV(cond, i, v)
#define PROFG(cond, i)

DEV u32 smem_u32(const void* p) { return (u32)__cvta_generic_to_shared(p); }
DEV void wg_fence() { asm volatile("wgmma.fence.sync.aligned;" ::: "memory"); }
DEV void wg_commit() { asm volatile("wgmma.commit_group.sync.aligned;" ::: "memory"); }
template <int N> DEV void wg_wait() { asm volatile("wgmma.wait_group.sync.aligned %0;" ::"n"(N) : "memory"); }
DEV u64 desc_join(u32 lo, u32 hi) { return ((u64)hi << 32) | lo; }
DEV constexpr u32 desc_lo(u32 addr, u32 lbo) { return ((addr & 0x3FFFF) >> 4) | ((lbo >> 4) << 16); }
DEV void mbar_init(u32 bar, int cnt) { asm volatile("mbarrier.init.shared::cta.b64 [%0], %1;" ::"r"(bar), "r"(cnt) : "memory"); }
DEV void mbar_arrive(u32 bar) { asm volatile("mbarrier.arrive.shared::cta.b64 _, [%0];" ::"r"(bar) : "memory"); }
DEV void mbar_arrive_if(u32 bar, bool c) { asm volatile("{\n.reg .pred p;\nsetp.ne.u32 p, %1, 0;\n@p mbarrier.arrive.shared::cta.b64 _, [%0];\n}\n" ::"r"(bar), "r"((u32)c) : "memory"); }
#define SAFE 0
#define SPIN(body) "W_LOOP:\n" body "@!p bra W_LOOP;\n"
DEV void mbar_wait(u32 bar, u32 parity) {
  asm volatile("{\n.reg .pred p, q;\n.reg .u32 n;\n" SPIN("mbarrier.try_wait.parity.shared::cta.b64 p, [%0], %1;\n") "}\n" ::"r"(bar), "r"(parity) : "memory");
}
DEV bool mbar_test(u32 bar, u32 parity) {
  u32 ok;
  asm volatile("{\n.reg .pred p;\nmbarrier.test_wait.parity.shared::cta.b64 p, [%1], %2;\nselp.u32 %0, 1, 0, p;\n}\n" : "=r"(ok) : "r"(bar), "r"(parity) : "memory");
  return ok;
}
DEV void trap_if_gt(int n, int lim) { asm volatile("{\n.reg .pred p;\nsetp.gt.s32 p, %0, %1;\n@p st.shared.u32 [%2], %0;\n}\n" ::"r"(n), "r"(lim), "r"(0x400000) : "memory"); }
DEV void until(u32 t0, int c) { while ((int)(clock() - t0) < c) {} }
DEV void bsync(int id, int n) { asm volatile("bar.sync %0, %1;" ::"r"(id), "r"(n) : "memory"); }
DEV bool bsync_and(int id, int n, bool v) {
  u32 r;
  asm volatile("{\n.reg .pred p, q;\nsetp.ne.u32 p, %3, 0;\nbarrier.red.and.aligned.pred q, %1, %2, p;\nselp.u32 %0, 1, 0, q;\n}\n" : "=r"(r) : "r"(id), "r"(n), "r"((u32)v) : "memory");
  return r;
}
DEV void barrive(int id, int n) { asm volatile("bar.arrive %0, %1;" ::"r"(id), "r"(n) : "memory"); }
DEV void fence_async_smem() { asm volatile("fence.proxy.async.shared::cta;" ::: "memory"); }
DEV void fence_gpu() { asm volatile("fence.acq_rel.gpu;" ::: "memory"); }
#define ELECT "{\n.reg .pred p;\nelect.sync _|p, 0xffffffff;\n"
DEV void e_init(u32 bar, int cnt) { asm volatile(ELECT "@p mbarrier.init.shared::cta.b64 [%0], %1;\n}\n" ::"r"(bar), "r"(cnt) : "memory"); }
DEV void e_init6(u32 b, int cnt) {
  asm volatile(ELECT "@p mbarrier.init.shared::cta.b64 [%0], 1;\n@p mbarrier.init.shared::cta.b64 [%0+96], 1;\n@p mbarrier.init.shared::cta.b64 [%0+192], 1;\n"
               "@p mbarrier.init.shared::cta.b64 [%0+288], 1;\n@p mbarrier.init.shared::cta.b64 [%0+480], 2;\n@p mbarrier.init.shared::cta.b64 [%0+576], %1;\n@p mbarrier.init.shared::cta.b64 [%0+672], 3;\n}\n" ::"r"(b), "r"(cnt) : "memory");
}
DEV void e_expect(u32 bar, u32 bytes) { asm volatile(ELECT "@p mbarrier.arrive.expect_tx.shared::cta.b64 _, [%0], %1;\n}\n" ::"r"(bar), "r"(bytes) : "memory"); }
DEV void e_arrive(u32 bar) { asm volatile(ELECT "@p mbarrier.arrive.shared::cta.b64 _, [%0];\n}\n" ::"r"(bar) : "memory"); }
DEV void e_load(u32 dst, const void* src, u32 bytes, u32 bar) {
  asm volatile(ELECT "@p cp.async.bulk.shared::cluster.global.mbarrier::complete_tx::bytes [%0], [%1], %2, [%3];\n}\n" ::"r"(dst), "l"(src), "r"(bytes), "r"(bar) : "memory");
}
DEV void e_xload(u32 dst, const void* src, u32 bytes, u32 bar) {
  asm volatile(ELECT "@p mbarrier.arrive.expect_tx.shared::cta.b64 _, [%3], %2;\n@p cp.async.bulk.shared::cluster.global.mbarrier::complete_tx::bytes [%0], [%1], %2, [%3];\n}\n"
               ::"r"(dst), "l"(src), "r"(bytes), "r"(bar) : "memory");
}
DEV void e_tma2d(u32 dst, const void* tm, u32 bar, int c0, int c1) {
  asm volatile(ELECT "@p cp.async.bulk.tensor.2d.shared::cluster.global.mbarrier::complete_tx::bytes [%0], [%1, {%3, %4}], [%2];\n}\n" ::"r"(dst), "l"(tm), "r"(bar), "r"(c0), "r"(c1) : "memory");
}
DEV void e_tma3d(u32 dst, const void* tm, u32 bar, int c0, int c1) {
  asm volatile(ELECT "@p cp.async.bulk.tensor.3d.shared::cluster.global.mbarrier::complete_tx::bytes [%0], [%1, {%3, %4, %5}], [%2];\n}\n" ::"r"(dst), "l"(tm), "r"(bar), "r"(c0), "r"(c1), "r"(0) : "memory");
}
DEV void e_pf3d(const void* tm, int c0, int c1) {
  asm volatile(ELECT "@p cp.async.bulk.prefetch.tensor.3d.L2.global [%0, {%1, %2, %3}];\n}\n" ::"l"(tm), "r"(c0), "r"(c1), "r"(0) : "memory");
}
#define WAIT_EXPECT "{\n.reg .pred p, q;\n.reg .u32 n;\n" SPIN("mbarrier.try_wait.parity.shared::cta.b64 p, [%0], %1;\n") \
  "elect.sync _|p, 0xffffffff;\n@p mbarrier.arrive.expect_tx.shared::cta.b64 _, [%2], %3;\n"
template <int BYTES> DEV void w_load(u32 be, u32 par, u32 bf, u32 dst, const void* src) {
  asm volatile(WAIT_EXPECT "@p cp.async.bulk.shared::cluster.global.mbarrier::complete_tx::bytes [%4], [%5], %3, [%2];\n}\n"
               ::"r"(be), "r"(par), "r"(bf), "n"(BYTES), "r"(dst), "l"(src) : "memory");
}
DEV void w_g1(u32 be, u32 par, u32 bf, u32 dst, const void* tm, int c0, int c1, const void* src) {
  asm volatile(WAIT_EXPECT "@p cp.async.bulk.tensor.3d.shared::cluster.global.mbarrier::complete_tx::bytes [%4], [%5, {%6, %7, %8}], [%2];\n"
               "@p cp.async.bulk.shared::cluster.global.mbarrier::complete_tx::bytes [%9], [%10], 11264, [%2];\n}\n"
               ::"r"(be), "r"(par), "r"(bf), "n"(BT), "r"(dst), "l"(tm), "r"(c0), "r"(c1), "r"(0), "r"(dst + 16384), "l"(src) : "memory");
}
DEV void w_g2(u32 be, u32 par, u32 bf, u32 db, const void* src, u32 da, const void* tm, int c0, int c1) {
  asm volatile(WAIT_EXPECT "@p cp.async.bulk.shared::cluster.global.mbarrier::complete_tx::bytes [%4], [%5], %10, [%2];\n"
               "@p cp.async.bulk.tensor.2d.shared::cluster.global.mbarrier::complete_tx::bytes [%6], [%7, {%8, %9}], [%2];\n}\n"
               ::"r"(be), "r"(par), "r"(bf), "n"(BT + 8192), "r"(db), "l"(src), "r"(da), "l"(tm), "r"(c0), "r"(c1), "n"(BT) : "memory");
}
DEV void load1d(u32 dst, const void* src, u32 bytes, u32 bar) {
  asm volatile("cp.async.bulk.shared::cluster.global.mbarrier::complete_tx::bytes [%0], [%1], %2, [%3];" ::"r"(dst), "l"(src), "r"(bytes), "r"(bar) : "memory");
}
DEV void pf2d(const void* tm, int c0, int c1) { asm volatile("cp.async.bulk.prefetch.tensor.2d.L2.global [%0, {%1, %2}];" ::"l"(tm), "r"(c0), "r"(c1) : "memory"); }
DEV void xtma2d(u32 dst, const void* tm, u32 bar, int c0, int c1, u32 bytes) {
  asm volatile("mbarrier.arrive.expect_tx.shared::cta.b64 _, [%2], %5;\ncp.async.bulk.tensor.2d.shared::cluster.global.mbarrier::complete_tx::bytes [%0], [%1, {%3, %4}], [%2];"
               ::"r"(dst), "l"(tm), "r"(bar), "r"(c0), "r"(c1), "r"(bytes) : "memory");
}
DEV void xload(u32 dst, const void* src, u32 bytes, u32 bar) {
  asm volatile("mbarrier.arrive.expect_tx.shared::cta.b64 _, [%3], %2;\ncp.async.bulk.shared::cluster.global.mbarrier::complete_tx::bytes [%0], [%1], %2, [%3];"
               ::"r"(dst), "l"(src), "r"(bytes), "r"(bar) : "memory");
}
DEV void e_prefetch(const void* src, u32 bytes) { asm volatile(ELECT "@p cp.async.bulk.prefetch.L2.global [%0], %1;\n}\n" ::"l"(src), "r"(bytes) : "memory"); }
DEV void e_tmpf(const void* tm) { asm volatile(ELECT "@p prefetch.tensormap [%0];\n}\n" ::"l"(tm) : "memory"); }
DEV uint4 ld_nc(const void* p) { uint4 v; asm volatile("ld.global.nc.v4.u32 {%0,%1,%2,%3}, [%4];" : "=r"(v.x), "=r"(v.y), "=r"(v.z), "=r"(v.w) : "l"(p)); return v; }
DEV void ldg128(u32* v, const void* p) { asm volatile("ld.global.cg.v4.u32 {%0,%1,%2,%3}, [%4];" : "=r"(v[0]), "=r"(v[1]), "=r"(v[2]), "=r"(v[3]) : "l"(p) : "memory"); }
DEV uint4 ld_rlx128(const void* p) {
  u64 a, b; asm volatile("ld.relaxed.gpu.global.v2.b64 {%0,%1}, [%2];" : "=l"(a), "=l"(b) : "l"(p) : "memory");
  return make_uint4((u32)a, (u32)(a >> 32), (u32)b, (u32)(b >> 32));
}
DEV uint2 ld_rlx64(const void* p) { u64 a; asm volatile("ld.relaxed.gpu.global.b64 %0, [%1];" : "=l"(a) : "l"(p) : "memory"); return make_uint2((u32)a, (u32)(a >> 32)); }
DEV void cp16(u32 dst, const void* src) { asm volatile("cp.async.cg.shared.global [%0], [%1], 16;" ::"r"(dst), "l"(src) : "memory"); }
DEV void cp_wait() { asm volatile("cp.async.wait_all;" ::: "memory"); }
DEV void bulk_store(void* dst, u32 src, u32 bytes) {
  asm volatile("cp.async.bulk.global.shared::cta.bulk_group [%0], [%1], %2;\ncp.async.bulk.commit_group;" ::"l"(dst), "r"(src), "r"(bytes) : "memory");
}
DEV void bulk_wait() { asm volatile("cp.async.bulk.wait_group 0;" ::: "memory"); }
DEV u32 ld_rlx32(const void* p) { u32 a; asm volatile("ld.relaxed.gpu.global.u32 %0, [%1];" : "=r"(a) : "l"(p) : "memory"); return a; }
DEV void ctr_arrive(u32* ctr, int f, u32 ep, u32 sel) {
  asm volatile("{\n.reg .pred p;\nsetp.eq.u32 p, %2, 0;\n@p red.relaxed.gpu.global.add.u32 [%0], %1;\n}\n"
               ::"l"(ctr + 1 + sel), "r"((1u - 2u * (ep & 1)) << (8 * f)), "r"(sel) : "memory");
}
DEV void ctr_poll(u32* ctr, int f, u32 ep, u32 n) {
  const u32 want = (ep & 1) ? 0 : n;
  int it = 0;
#pragma unroll 1
  while (__any_sync(0xffffffffu, ((ld_rlx32(ctr + 1) >> (8 * f)) & 255) != want)) trap_if_gt(++it, 1 << 20);
}
DEV void stamp_post(u32* ctr, u32 ep, int i, u32 t0, u32 sel) {
  asm volatile("{\n.reg .pred p;\nsetp.eq.u32 p, %2, 0;\n@p red.relaxed.gpu.global.max.u32 [%0+4], %1;\n@p red.relaxed.gpu.global.add.u32 [%0], 1;\n}\n"
               ::"l"(ctr + 8 + 8 * (ep & 1) + 2 * i + sel), "r"((u32)clock() - t0), "r"(sel) : "memory");
}
DEV int stamp_wait(u32* ctr, u32 ep, int i) {
  uint2 v = make_uint2(0, 0);
  int it = 0;
#pragma unroll 1
  while (__any_sync(0xffffffffu, v.x != 128)) { v = ld_rlx64(ctr + 8 + 8 * (ep & 1) + 2 * i); trap_if_gt(++it, 1 << 20); }
  return v.y;
}
DEV void tile_post(u32* w, u32 t0, u32 ep, bool c) { if (c) asm volatile("st.relaxed.gpu.global.u32 [%0], %1;" ::"l"(w), "r"(min((u32)clock() - t0, 0xfffffu) ^ ((ep + 1) << 20)) : "memory"); }
DEV int tile_wait(const u32* w, u32 ep) {
  u32 m;
  int it = 0;
#pragma unroll 1
  do {
    const uint2 a = ld_rlx64(w), b = ld_rlx64(w + 2);
    const u32 e = (ep + 1) << 20;
    m = max(max(a.x ^ e, a.y ^ e), max(b.x ^ e, b.y ^ e));
    trap_if_gt(++it, 1 << 20);
  } while (__any_sync(0xffffffffu, m >> 20));
  return m;
}
DEV void stg128(void* p, uint4 v) { asm volatile("st.global.v4.b32 [%0], {%1,%2,%3,%4};" ::"l"(p), "r"(v.x), "r"(v.y), "r"(v.z), "r"(v.w) : "memory"); }
DEV void stg32(void* p, u32 v) { asm volatile("st.global.b32 [%0], %1;" ::"l"(p), "r"(v) : "memory"); }
DEV void stg32_if(void* p, u32 v, bool c) { asm volatile("{\n.reg .pred q;\nsetp.ne.u32 q, %2, 0;\n@q st.global.b32 [%0], %1;\n}\n" ::"l"(p), "r"(v), "r"((u32)c) : "memory"); }
DEV u32 lds32(u32 a) { u32 v; asm volatile("ld.shared.b32 %0, [%1];" : "=r"(v) : "r"(a) : "memory"); return v; }
DEV void lds64(u32* v, u32 a) { asm volatile("ld.shared.v2.b32 {%0,%1}, [%2];" : "=r"(v[0]), "=r"(v[1]) : "r"(a) : "memory"); }
DEV uint4 lds128(u32 a) { uint4 v; asm volatile("ld.shared.v4.b32 {%0,%1,%2,%3}, [%4];" : "=r"(v.x), "=r"(v.y), "=r"(v.z), "=r"(v.w) : "r"(a) : "memory"); return v; }
DEV void lds128(u32* v, u32 a) { asm volatile("ld.shared.v4.b32 {%0,%1,%2,%3}, [%4];" : "=r"(v[0]), "=r"(v[1]), "=r"(v[2]), "=r"(v[3]) : "r"(a) : "memory"); }
DEV void sts16(u32 a, u32 v) { asm volatile("st.shared.b16 [%0], %1;" ::"r"(a), "h"((u16)v) : "memory"); }
DEV void sts32(u32 a, u32 v) { asm volatile("st.shared.b32 [%0], %1;" ::"r"(a), "r"(v) : "memory"); }
DEV void sts64f(u32 a, float x, float y) { asm volatile("st.shared.v2.f32 [%0], {%1,%2};" ::"r"(a), "f"(x), "f"(y) : "memory"); }
DEV void sts128(u32 a, uint4 v) { asm volatile("st.shared.v4.b32 [%0], {%1,%2,%3,%4};" ::"r"(a), "r"(v.x), "r"(v.y), "r"(v.z), "r"(v.w) : "memory"); }
DEV void consume(u32 x) { asm volatile("{\n.reg .pred p;\nsetp.eq.u32 p, %0, 0x7fc12345;\n@p nanosleep.u32 0;\n}\n" ::"r"(x) : "memory"); }
DEV int lane_now() { int l; asm volatile("mov.u32 %0, %%laneid;" : "=r"(l)); return l; }
DEV u32 opaque(u32 x) { asm volatile("" : "+r"(x)); return x; }
DEV void ldsm4(u32* r, u32 a) { asm volatile("ldmatrix.sync.aligned.m8n8.x4.shared.b16 {%0,%1,%2,%3}, [%4];" : "=r"(r[0]), "=r"(r[1]), "=r"(r[2]), "=r"(r[3]) : "r"(a) : "memory"); }
DEV void ldsm4t(u32* r, u32 a) { asm volatile("ldmatrix.sync.aligned.m8n8.x4.trans.shared.b16 {%0,%1,%2,%3}, [%4];" : "=r"(r[0]), "=r"(r[1]), "=r"(r[2]), "=r"(r[3]) : "r"(a) : "memory"); }
DEV void stsm4(u32 a, const u32* r) { asm volatile("stmatrix.sync.aligned.m8n8.x4.shared.b16 [%0], {%1,%2,%3,%4};" ::"r"(a), "r"(r[0]), "r"(r[1]), "r"(r[2]), "r"(r[3]) : "memory"); }
DEV void stsm4t(u32 a, const u32* r) { asm volatile("stmatrix.sync.aligned.m8n8.x4.trans.shared.b16 [%0], {%1,%2,%3,%4};" ::"r"(a), "r"(r[0]), "r"(r[1]), "r"(r[2]), "r"(r[3]) : "memory"); }
DEV void stsm2(u32 a, u32 r0, u32 r1) { asm volatile("stmatrix.sync.aligned.m8n8.x2.shared.b16 [%0], {%1,%2};" ::"r"(a), "r"(r0), "r"(r1) : "memory"); }
DEV void mma16816(float* c, u32 a0, u32 a1, u32 a2, u32 a3, u32 b0, u32 b1) {
  asm volatile("mma.sync.aligned.m16n8k16.row.col.f32.bf16.bf16.f32 {%0,%1,%2,%3}, {%4,%5,%6,%7}, {%8,%9}, {%0,%1,%2,%3};"
      : "+f"(c[0]), "+f"(c[1]), "+f"(c[2]), "+f"(c[3]) : "r"(a0), "r"(a1), "r"(a2), "r"(a3), "r"(b0), "r"(b1));
}
constexpr u32 ONE2 = 0x3f803f80u;
DEV u32 prmt(u32 a, u32 b, u32 s) { u32 r; asm("prmt.b32 %0, %1, %2, %3;" : "=r"(r) : "r"(a), "r"(b), "r"(s)); return r; }
DEV u32 hmul2(u32 a, u32 b) { u32 r; asm("mul.rn.bf16x2 %0, %1, %2;" : "=r"(r) : "r"(a), "r"(b)); return r; }
DEV u32 hadd2(u32 a, u32 b) { u32 r; asm("add.rn.bf16x2 %0, %1, %2;" : "=r"(r) : "r"(a), "r"(b)); return r; }
DEV u32 hfma2(u32 a, u32 b, u32 c) { u32 r; asm("fma.rn.bf16x2 %0, %1, %2, %3;" : "=r"(r) : "r"(a), "r"(b), "r"(c)); return r; }
DEV void row_stats(float (*c)[4], const u32* x) {
  mma16816(c[0], x[0], x[1], x[2], x[3], ONE2, ONE2);
  mma16816(c[1], x[0], x[1], x[2], x[3], x[0], x[2]);
  mma16816(c[2], x[0], x[1], x[2], x[3], x[1], x[3]);
}
DEV u32 pack2(float lo, float hi) { u32 r; asm("cvt.rn.bf16x2.f32 %0, %1, %2;" : "=r"(r) : "f"(hi), "f"(lo)); return r; }
DEV float bflo(u32 w) { return __uint_as_float(w * 65536u); }
DEV float bfhi(u32 w) { return __uint_as_float(w & 0xffff0000u); }
DEV u32 tagw(u32 w, u32 m, u32 par) { return (w & ~m) | (par & m); }
DEV u32 nz(u32 w) { return max(w, 1u); }
DEV float rsq(float x) { float r; asm("rsqrt.approx.ftz.f32 %0, %1;" : "=f"(r) : "f"(x)); return r; }
DEV float tanh_fast(float x) { float r; asm("tanh.approx.f32 %0, %1;" : "=f"(r) : "f"(x)); return r; }
DEV float shx(float v, int m) { return __shfl_xor_sync(0xffffffffu, v, m); }
DEV void wgmma_ss_128(float* d, u64 da, u64 db, int sd) {
  asm volatile("{\n.reg .pred p;\nsetp.ne.b32 p, %66, 0;\nwgmma.mma_async.sync.aligned.m64n128k16.f32.bf16.bf16 {%0, %1, %2, %3, %4, %5, %6, %7, %8, %9, %10, %11, %12, %13, %14, %15, %16, %17, %18, %19, %20, %21, %22, %23, %24, %25, %26, %27, %28, %29, %30, %31, %32, %33, %34, %35, %36, %37, %38, %39, %40, %41, %42, %43, %44, %45, %46, %47, %48, %49, %50, %51, %52, %53, %54, %55, %56, %57, %58, %59, %60, %61, %62, %63}, %64, %65, p, 1, 1, 0, 1;\n}\n"
    : "+f"(d[0]), "+f"(d[1]), "+f"(d[2]), "+f"(d[3]), "+f"(d[4]), "+f"(d[5]), "+f"(d[6]), "+f"(d[7]), "+f"(d[8]), "+f"(d[9]), "+f"(d[10]), "+f"(d[11]), "+f"(d[12]), "+f"(d[13]), "+f"(d[14]), "+f"(d[15]), "+f"(d[16]), "+f"(d[17]), "+f"(d[18]), "+f"(d[19]), "+f"(d[20]), "+f"(d[21]), "+f"(d[22]), "+f"(d[23]), "+f"(d[24]), "+f"(d[25]), "+f"(d[26]), "+f"(d[27]), "+f"(d[28]), "+f"(d[29]), "+f"(d[30]), "+f"(d[31]), "+f"(d[32]), "+f"(d[33]), "+f"(d[34]), "+f"(d[35]), "+f"(d[36]), "+f"(d[37]), "+f"(d[38]), "+f"(d[39]), "+f"(d[40]), "+f"(d[41]), "+f"(d[42]), "+f"(d[43]), "+f"(d[44]), "+f"(d[45]), "+f"(d[46]), "+f"(d[47]), "+f"(d[48]), "+f"(d[49]), "+f"(d[50]), "+f"(d[51]), "+f"(d[52]), "+f"(d[53]), "+f"(d[54]), "+f"(d[55]), "+f"(d[56]), "+f"(d[57]), "+f"(d[58]), "+f"(d[59]), "+f"(d[60]), "+f"(d[61]), "+f"(d[62]), "+f"(d[63]) : "l"(da), "l"(db), "r"(sd));
}
DEV void wgmma_ss_88(float* d, u64 da, u64 db, int sd) {
  asm volatile("{\n.reg .pred p;\nsetp.ne.b32 p, %46, 0;\nwgmma.mma_async.sync.aligned.m64n88k16.f32.bf16.bf16 {%0, %1, %2, %3, %4, %5, %6, %7, %8, %9, %10, %11, %12, %13, %14, %15, %16, %17, %18, %19, %20, %21, %22, %23, %24, %25, %26, %27, %28, %29, %30, %31, %32, %33, %34, %35, %36, %37, %38, %39, %40, %41, %42, %43}, %44, %45, p, 1, 1, 0, 1;\n}\n"
    : "+f"(d[0]), "+f"(d[1]), "+f"(d[2]), "+f"(d[3]), "+f"(d[4]), "+f"(d[5]), "+f"(d[6]), "+f"(d[7]), "+f"(d[8]), "+f"(d[9]), "+f"(d[10]), "+f"(d[11]), "+f"(d[12]), "+f"(d[13]), "+f"(d[14]), "+f"(d[15]), "+f"(d[16]), "+f"(d[17]), "+f"(d[18]), "+f"(d[19]), "+f"(d[20]), "+f"(d[21]), "+f"(d[22]), "+f"(d[23]), "+f"(d[24]), "+f"(d[25]), "+f"(d[26]), "+f"(d[27]), "+f"(d[28]), "+f"(d[29]), "+f"(d[30]), "+f"(d[31]), "+f"(d[32]), "+f"(d[33]), "+f"(d[34]), "+f"(d[35]), "+f"(d[36]), "+f"(d[37]), "+f"(d[38]), "+f"(d[39]), "+f"(d[40]), "+f"(d[41]), "+f"(d[42]), "+f"(d[43]) : "l"(da), "l"(db), "r"(sd));
}
DEV void wgmma_ss_160(float* d, u64 da, u64 db, int sd) {
  asm volatile("{\n.reg .pred p;\nsetp.ne.b32 p, %82, 0;\nwgmma.mma_async.sync.aligned.m64n160k16.f32.bf16.bf16 {%0, %1, %2, %3, %4, %5, %6, %7, %8, %9, %10, %11, %12, %13, %14, %15, %16, %17, %18, %19, %20, %21, %22, %23, %24, %25, %26, %27, %28, %29, %30, %31, %32, %33, %34, %35, %36, %37, %38, %39, %40, %41, %42, %43, %44, %45, %46, %47, %48, %49, %50, %51, %52, %53, %54, %55, %56, %57, %58, %59, %60, %61, %62, %63, %64, %65, %66, %67, %68, %69, %70, %71, %72, %73, %74, %75, %76, %77, %78, %79}, %80, %81, p, 1, 1, 0, 1;\n}\n"
    : "+f"(d[0]), "+f"(d[1]), "+f"(d[2]), "+f"(d[3]), "+f"(d[4]), "+f"(d[5]), "+f"(d[6]), "+f"(d[7]), "+f"(d[8]), "+f"(d[9]), "+f"(d[10]), "+f"(d[11]), "+f"(d[12]), "+f"(d[13]), "+f"(d[14]), "+f"(d[15]), "+f"(d[16]), "+f"(d[17]), "+f"(d[18]), "+f"(d[19]), "+f"(d[20]), "+f"(d[21]), "+f"(d[22]), "+f"(d[23]), "+f"(d[24]), "+f"(d[25]), "+f"(d[26]), "+f"(d[27]), "+f"(d[28]), "+f"(d[29]), "+f"(d[30]), "+f"(d[31]), "+f"(d[32]), "+f"(d[33]), "+f"(d[34]), "+f"(d[35]), "+f"(d[36]), "+f"(d[37]), "+f"(d[38]), "+f"(d[39]), "+f"(d[40]), "+f"(d[41]), "+f"(d[42]), "+f"(d[43]), "+f"(d[44]), "+f"(d[45]), "+f"(d[46]), "+f"(d[47]), "+f"(d[48]), "+f"(d[49]), "+f"(d[50]), "+f"(d[51]), "+f"(d[52]), "+f"(d[53]), "+f"(d[54]), "+f"(d[55]), "+f"(d[56]), "+f"(d[57]), "+f"(d[58]), "+f"(d[59]), "+f"(d[60]), "+f"(d[61]), "+f"(d[62]), "+f"(d[63]), "+f"(d[64]), "+f"(d[65]), "+f"(d[66]), "+f"(d[67]), "+f"(d[68]), "+f"(d[69]), "+f"(d[70]), "+f"(d[71]), "+f"(d[72]), "+f"(d[73]), "+f"(d[74]), "+f"(d[75]), "+f"(d[76]), "+f"(d[77]), "+f"(d[78]), "+f"(d[79]) : "l"(da), "l"(db), "r"(sd));
}
DEV void wgmma_rs_160(float* d, const u32* a, u64 db, int sd) {
  asm volatile("{\n.reg .pred p;\nsetp.ne.b32 p, %85, 0;\nwgmma.mma_async.sync.aligned.m64n160k16.f32.bf16.bf16 {%0, %1, %2, %3, %4, %5, %6, %7, %8, %9, %10, %11, %12, %13, %14, %15, %16, %17, %18, %19, %20, %21, %22, %23, %24, %25, %26, %27, %28, %29, %30, %31, %32, %33, %34, %35, %36, %37, %38, %39, %40, %41, %42, %43, %44, %45, %46, %47, %48, %49, %50, %51, %52, %53, %54, %55, %56, %57, %58, %59, %60, %61, %62, %63, %64, %65, %66, %67, %68, %69, %70, %71, %72, %73, %74, %75, %76, %77, %78, %79}, {%80, %81, %82, %83}, %84, p, 1, 1, 1;\n}\n"
    : "+f"(d[0]), "+f"(d[1]), "+f"(d[2]), "+f"(d[3]), "+f"(d[4]), "+f"(d[5]), "+f"(d[6]), "+f"(d[7]), "+f"(d[8]), "+f"(d[9]), "+f"(d[10]), "+f"(d[11]), "+f"(d[12]), "+f"(d[13]), "+f"(d[14]), "+f"(d[15]), "+f"(d[16]), "+f"(d[17]), "+f"(d[18]), "+f"(d[19]), "+f"(d[20]), "+f"(d[21]), "+f"(d[22]), "+f"(d[23]), "+f"(d[24]), "+f"(d[25]), "+f"(d[26]), "+f"(d[27]), "+f"(d[28]), "+f"(d[29]), "+f"(d[30]), "+f"(d[31]), "+f"(d[32]), "+f"(d[33]), "+f"(d[34]), "+f"(d[35]), "+f"(d[36]), "+f"(d[37]), "+f"(d[38]), "+f"(d[39]), "+f"(d[40]), "+f"(d[41]), "+f"(d[42]), "+f"(d[43]), "+f"(d[44]), "+f"(d[45]), "+f"(d[46]), "+f"(d[47]), "+f"(d[48]), "+f"(d[49]), "+f"(d[50]), "+f"(d[51]), "+f"(d[52]), "+f"(d[53]), "+f"(d[54]), "+f"(d[55]), "+f"(d[56]), "+f"(d[57]), "+f"(d[58]), "+f"(d[59]), "+f"(d[60]), "+f"(d[61]), "+f"(d[62]), "+f"(d[63]), "+f"(d[64]), "+f"(d[65]), "+f"(d[66]), "+f"(d[67]), "+f"(d[68]), "+f"(d[69]), "+f"(d[70]), "+f"(d[71]), "+f"(d[72]), "+f"(d[73]), "+f"(d[74]), "+f"(d[75]), "+f"(d[76]), "+f"(d[77]), "+f"(d[78]), "+f"(d[79]) : "r"(a[0]), "r"(a[1]), "r"(a[2]), "r"(a[3]), "l"(db), "r"(sd));
}
template <int N> DEV void wgmma_rs(float* d, const u32* a, u64 db);
template <> DEV void wgmma_rs<256>(float* d, const u32* a, u64 db) {
  asm volatile("wgmma.mma_async.sync.aligned.m64n256k16.f32.bf16.bf16 {%0, %1, %2, %3, %4, %5, %6, %7, %8, %9, %10, %11, %12, %13, %14, %15, %16, %17, %18, %19, %20, %21, %22, %23, %24, %25, %26, %27, %28, %29, %30, %31, %32, %33, %34, %35, %36, %37, %38, %39, %40, %41, %42, %43, %44, %45, %46, %47, %48, %49, %50, %51, %52, %53, %54, %55, %56, %57, %58, %59, %60, %61, %62, %63, %64, %65, %66, %67, %68, %69, %70, %71, %72, %73, %74, %75, %76, %77, %78, %79, %80, %81, %82, %83, %84, %85, %86, %87, %88, %89, %90, %91, %92, %93, %94, %95, %96, %97, %98, %99, %100, %101, %102, %103, %104, %105, %106, %107, %108, %109, %110, %111, %112, %113, %114, %115, %116, %117, %118, %119, %120, %121, %122, %123, %124, %125, %126, %127}, {%128, %129, %130, %131}, %132, 0, 1, 1, 0;"
    : "+f"(d[0]), "+f"(d[1]), "+f"(d[2]), "+f"(d[3]), "+f"(d[4]), "+f"(d[5]), "+f"(d[6]), "+f"(d[7]), "+f"(d[8]), "+f"(d[9]), "+f"(d[10]), "+f"(d[11]), "+f"(d[12]), "+f"(d[13]), "+f"(d[14]), "+f"(d[15]), "+f"(d[16]), "+f"(d[17]), "+f"(d[18]), "+f"(d[19]), "+f"(d[20]), "+f"(d[21]), "+f"(d[22]), "+f"(d[23]), "+f"(d[24]), "+f"(d[25]), "+f"(d[26]), "+f"(d[27]), "+f"(d[28]), "+f"(d[29]), "+f"(d[30]), "+f"(d[31]), "+f"(d[32]), "+f"(d[33]), "+f"(d[34]), "+f"(d[35]), "+f"(d[36]), "+f"(d[37]), "+f"(d[38]), "+f"(d[39]), "+f"(d[40]), "+f"(d[41]), "+f"(d[42]), "+f"(d[43]), "+f"(d[44]), "+f"(d[45]), "+f"(d[46]), "+f"(d[47]), "+f"(d[48]), "+f"(d[49]), "+f"(d[50]), "+f"(d[51]), "+f"(d[52]), "+f"(d[53]), "+f"(d[54]), "+f"(d[55]), "+f"(d[56]), "+f"(d[57]), "+f"(d[58]), "+f"(d[59]), "+f"(d[60]), "+f"(d[61]), "+f"(d[62]), "+f"(d[63]), "+f"(d[64]), "+f"(d[65]), "+f"(d[66]), "+f"(d[67]), "+f"(d[68]), "+f"(d[69]), "+f"(d[70]), "+f"(d[71]), "+f"(d[72]), "+f"(d[73]), "+f"(d[74]), "+f"(d[75]), "+f"(d[76]), "+f"(d[77]), "+f"(d[78]), "+f"(d[79]), "+f"(d[80]), "+f"(d[81]), "+f"(d[82]), "+f"(d[83]), "+f"(d[84]), "+f"(d[85]), "+f"(d[86]), "+f"(d[87]), "+f"(d[88]), "+f"(d[89]), "+f"(d[90]), "+f"(d[91]), "+f"(d[92]), "+f"(d[93]), "+f"(d[94]), "+f"(d[95]), "+f"(d[96]), "+f"(d[97]), "+f"(d[98]), "+f"(d[99]), "+f"(d[100]), "+f"(d[101]), "+f"(d[102]), "+f"(d[103]), "+f"(d[104]), "+f"(d[105]), "+f"(d[106]), "+f"(d[107]), "+f"(d[108]), "+f"(d[109]), "+f"(d[110]), "+f"(d[111]), "+f"(d[112]), "+f"(d[113]), "+f"(d[114]), "+f"(d[115]), "+f"(d[116]), "+f"(d[117]), "+f"(d[118]), "+f"(d[119]), "+f"(d[120]), "+f"(d[121]), "+f"(d[122]), "+f"(d[123]), "+f"(d[124]), "+f"(d[125]), "+f"(d[126]), "+f"(d[127]) : "r"(a[0]), "r"(a[1]), "r"(a[2]), "r"(a[3]), "l"(db));
}
template <> DEV void wgmma_rs<240>(float* d, const u32* a, u64 db) {
  asm volatile("wgmma.mma_async.sync.aligned.m64n240k16.f32.bf16.bf16 {%0, %1, %2, %3, %4, %5, %6, %7, %8, %9, %10, %11, %12, %13, %14, %15, %16, %17, %18, %19, %20, %21, %22, %23, %24, %25, %26, %27, %28, %29, %30, %31, %32, %33, %34, %35, %36, %37, %38, %39, %40, %41, %42, %43, %44, %45, %46, %47, %48, %49, %50, %51, %52, %53, %54, %55, %56, %57, %58, %59, %60, %61, %62, %63, %64, %65, %66, %67, %68, %69, %70, %71, %72, %73, %74, %75, %76, %77, %78, %79, %80, %81, %82, %83, %84, %85, %86, %87, %88, %89, %90, %91, %92, %93, %94, %95, %96, %97, %98, %99, %100, %101, %102, %103, %104, %105, %106, %107, %108, %109, %110, %111, %112, %113, %114, %115, %116, %117, %118, %119}, {%120, %121, %122, %123}, %124, 1, 1, 1, 0;"
    : "+f"(d[0]), "+f"(d[1]), "+f"(d[2]), "+f"(d[3]), "+f"(d[4]), "+f"(d[5]), "+f"(d[6]), "+f"(d[7]), "+f"(d[8]), "+f"(d[9]), "+f"(d[10]), "+f"(d[11]), "+f"(d[12]), "+f"(d[13]), "+f"(d[14]), "+f"(d[15]), "+f"(d[16]), "+f"(d[17]), "+f"(d[18]), "+f"(d[19]), "+f"(d[20]), "+f"(d[21]), "+f"(d[22]), "+f"(d[23]), "+f"(d[24]), "+f"(d[25]), "+f"(d[26]), "+f"(d[27]), "+f"(d[28]), "+f"(d[29]), "+f"(d[30]), "+f"(d[31]), "+f"(d[32]), "+f"(d[33]), "+f"(d[34]), "+f"(d[35]), "+f"(d[36]), "+f"(d[37]), "+f"(d[38]), "+f"(d[39]), "+f"(d[40]), "+f"(d[41]), "+f"(d[42]), "+f"(d[43]), "+f"(d[44]), "+f"(d[45]), "+f"(d[46]), "+f"(d[47]), "+f"(d[48]), "+f"(d[49]), "+f"(d[50]), "+f"(d[51]), "+f"(d[52]), "+f"(d[53]), "+f"(d[54]), "+f"(d[55]), "+f"(d[56]), "+f"(d[57]), "+f"(d[58]), "+f"(d[59]), "+f"(d[60]), "+f"(d[61]), "+f"(d[62]), "+f"(d[63]), "+f"(d[64]), "+f"(d[65]), "+f"(d[66]), "+f"(d[67]), "+f"(d[68]), "+f"(d[69]), "+f"(d[70]), "+f"(d[71]), "+f"(d[72]), "+f"(d[73]), "+f"(d[74]), "+f"(d[75]), "+f"(d[76]), "+f"(d[77]), "+f"(d[78]), "+f"(d[79]), "+f"(d[80]), "+f"(d[81]), "+f"(d[82]), "+f"(d[83]), "+f"(d[84]), "+f"(d[85]), "+f"(d[86]), "+f"(d[87]), "+f"(d[88]), "+f"(d[89]), "+f"(d[90]), "+f"(d[91]), "+f"(d[92]), "+f"(d[93]), "+f"(d[94]), "+f"(d[95]), "+f"(d[96]), "+f"(d[97]), "+f"(d[98]), "+f"(d[99]), "+f"(d[100]), "+f"(d[101]), "+f"(d[102]), "+f"(d[103]), "+f"(d[104]), "+f"(d[105]), "+f"(d[106]), "+f"(d[107]), "+f"(d[108]), "+f"(d[109]), "+f"(d[110]), "+f"(d[111]), "+f"(d[112]), "+f"(d[113]), "+f"(d[114]), "+f"(d[115]), "+f"(d[116]), "+f"(d[117]), "+f"(d[118]), "+f"(d[119]) : "r"(a[0]), "r"(a[1]), "r"(a[2]), "r"(a[3]), "l"(db));
}
template <> DEV void wgmma_rs<224>(float* d, const u32* a, u64 db) {
  asm volatile("wgmma.mma_async.sync.aligned.m64n224k16.f32.bf16.bf16 {%0, %1, %2, %3, %4, %5, %6, %7, %8, %9, %10, %11, %12, %13, %14, %15, %16, %17, %18, %19, %20, %21, %22, %23, %24, %25, %26, %27, %28, %29, %30, %31, %32, %33, %34, %35, %36, %37, %38, %39, %40, %41, %42, %43, %44, %45, %46, %47, %48, %49, %50, %51, %52, %53, %54, %55, %56, %57, %58, %59, %60, %61, %62, %63, %64, %65, %66, %67, %68, %69, %70, %71, %72, %73, %74, %75, %76, %77, %78, %79, %80, %81, %82, %83, %84, %85, %86, %87, %88, %89, %90, %91, %92, %93, %94, %95, %96, %97, %98, %99, %100, %101, %102, %103, %104, %105, %106, %107, %108, %109, %110, %111}, {%112, %113, %114, %115}, %116, 1, 1, 1, 0;"
    : "+f"(d[0]), "+f"(d[1]), "+f"(d[2]), "+f"(d[3]), "+f"(d[4]), "+f"(d[5]), "+f"(d[6]), "+f"(d[7]), "+f"(d[8]), "+f"(d[9]), "+f"(d[10]), "+f"(d[11]), "+f"(d[12]), "+f"(d[13]), "+f"(d[14]), "+f"(d[15]), "+f"(d[16]), "+f"(d[17]), "+f"(d[18]), "+f"(d[19]), "+f"(d[20]), "+f"(d[21]), "+f"(d[22]), "+f"(d[23]), "+f"(d[24]), "+f"(d[25]), "+f"(d[26]), "+f"(d[27]), "+f"(d[28]), "+f"(d[29]), "+f"(d[30]), "+f"(d[31]), "+f"(d[32]), "+f"(d[33]), "+f"(d[34]), "+f"(d[35]), "+f"(d[36]), "+f"(d[37]), "+f"(d[38]), "+f"(d[39]), "+f"(d[40]), "+f"(d[41]), "+f"(d[42]), "+f"(d[43]), "+f"(d[44]), "+f"(d[45]), "+f"(d[46]), "+f"(d[47]), "+f"(d[48]), "+f"(d[49]), "+f"(d[50]), "+f"(d[51]), "+f"(d[52]), "+f"(d[53]), "+f"(d[54]), "+f"(d[55]), "+f"(d[56]), "+f"(d[57]), "+f"(d[58]), "+f"(d[59]), "+f"(d[60]), "+f"(d[61]), "+f"(d[62]), "+f"(d[63]), "+f"(d[64]), "+f"(d[65]), "+f"(d[66]), "+f"(d[67]), "+f"(d[68]), "+f"(d[69]), "+f"(d[70]), "+f"(d[71]), "+f"(d[72]), "+f"(d[73]), "+f"(d[74]), "+f"(d[75]), "+f"(d[76]), "+f"(d[77]), "+f"(d[78]), "+f"(d[79]), "+f"(d[80]), "+f"(d[81]), "+f"(d[82]), "+f"(d[83]), "+f"(d[84]), "+f"(d[85]), "+f"(d[86]), "+f"(d[87]), "+f"(d[88]), "+f"(d[89]), "+f"(d[90]), "+f"(d[91]), "+f"(d[92]), "+f"(d[93]), "+f"(d[94]), "+f"(d[95]), "+f"(d[96]), "+f"(d[97]), "+f"(d[98]), "+f"(d[99]), "+f"(d[100]), "+f"(d[101]), "+f"(d[102]), "+f"(d[103]), "+f"(d[104]), "+f"(d[105]), "+f"(d[106]), "+f"(d[107]), "+f"(d[108]), "+f"(d[109]), "+f"(d[110]), "+f"(d[111]) : "r"(a[0]), "r"(a[1]), "r"(a[2]), "r"(a[3]), "l"(db));
}
template <> DEV void wgmma_rs<208>(float* d, const u32* a, u64 db) {
  asm volatile("wgmma.mma_async.sync.aligned.m64n208k16.f32.bf16.bf16 {%0, %1, %2, %3, %4, %5, %6, %7, %8, %9, %10, %11, %12, %13, %14, %15, %16, %17, %18, %19, %20, %21, %22, %23, %24, %25, %26, %27, %28, %29, %30, %31, %32, %33, %34, %35, %36, %37, %38, %39, %40, %41, %42, %43, %44, %45, %46, %47, %48, %49, %50, %51, %52, %53, %54, %55, %56, %57, %58, %59, %60, %61, %62, %63, %64, %65, %66, %67, %68, %69, %70, %71, %72, %73, %74, %75, %76, %77, %78, %79, %80, %81, %82, %83, %84, %85, %86, %87, %88, %89, %90, %91, %92, %93, %94, %95, %96, %97, %98, %99, %100, %101, %102, %103}, {%104, %105, %106, %107}, %108, 1, 1, 1, 0;"
    : "+f"(d[0]), "+f"(d[1]), "+f"(d[2]), "+f"(d[3]), "+f"(d[4]), "+f"(d[5]), "+f"(d[6]), "+f"(d[7]), "+f"(d[8]), "+f"(d[9]), "+f"(d[10]), "+f"(d[11]), "+f"(d[12]), "+f"(d[13]), "+f"(d[14]), "+f"(d[15]), "+f"(d[16]), "+f"(d[17]), "+f"(d[18]), "+f"(d[19]), "+f"(d[20]), "+f"(d[21]), "+f"(d[22]), "+f"(d[23]), "+f"(d[24]), "+f"(d[25]), "+f"(d[26]), "+f"(d[27]), "+f"(d[28]), "+f"(d[29]), "+f"(d[30]), "+f"(d[31]), "+f"(d[32]), "+f"(d[33]), "+f"(d[34]), "+f"(d[35]), "+f"(d[36]), "+f"(d[37]), "+f"(d[38]), "+f"(d[39]), "+f"(d[40]), "+f"(d[41]), "+f"(d[42]), "+f"(d[43]), "+f"(d[44]), "+f"(d[45]), "+f"(d[46]), "+f"(d[47]), "+f"(d[48]), "+f"(d[49]), "+f"(d[50]), "+f"(d[51]), "+f"(d[52]), "+f"(d[53]), "+f"(d[54]), "+f"(d[55]), "+f"(d[56]), "+f"(d[57]), "+f"(d[58]), "+f"(d[59]), "+f"(d[60]), "+f"(d[61]), "+f"(d[62]), "+f"(d[63]), "+f"(d[64]), "+f"(d[65]), "+f"(d[66]), "+f"(d[67]), "+f"(d[68]), "+f"(d[69]), "+f"(d[70]), "+f"(d[71]), "+f"(d[72]), "+f"(d[73]), "+f"(d[74]), "+f"(d[75]), "+f"(d[76]), "+f"(d[77]), "+f"(d[78]), "+f"(d[79]), "+f"(d[80]), "+f"(d[81]), "+f"(d[82]), "+f"(d[83]), "+f"(d[84]), "+f"(d[85]), "+f"(d[86]), "+f"(d[87]), "+f"(d[88]), "+f"(d[89]), "+f"(d[90]), "+f"(d[91]), "+f"(d[92]), "+f"(d[93]), "+f"(d[94]), "+f"(d[95]), "+f"(d[96]), "+f"(d[97]), "+f"(d[98]), "+f"(d[99]), "+f"(d[100]), "+f"(d[101]), "+f"(d[102]), "+f"(d[103]) : "r"(a[0]), "r"(a[1]), "r"(a[2]), "r"(a[3]), "l"(db));
}
template <> DEV void wgmma_rs<192>(float* d, const u32* a, u64 db) {
  asm volatile("wgmma.mma_async.sync.aligned.m64n192k16.f32.bf16.bf16 {%0, %1, %2, %3, %4, %5, %6, %7, %8, %9, %10, %11, %12, %13, %14, %15, %16, %17, %18, %19, %20, %21, %22, %23, %24, %25, %26, %27, %28, %29, %30, %31, %32, %33, %34, %35, %36, %37, %38, %39, %40, %41, %42, %43, %44, %45, %46, %47, %48, %49, %50, %51, %52, %53, %54, %55, %56, %57, %58, %59, %60, %61, %62, %63, %64, %65, %66, %67, %68, %69, %70, %71, %72, %73, %74, %75, %76, %77, %78, %79, %80, %81, %82, %83, %84, %85, %86, %87, %88, %89, %90, %91, %92, %93, %94, %95}, {%96, %97, %98, %99}, %100, 1, 1, 1, 0;"
    : "+f"(d[0]), "+f"(d[1]), "+f"(d[2]), "+f"(d[3]), "+f"(d[4]), "+f"(d[5]), "+f"(d[6]), "+f"(d[7]), "+f"(d[8]), "+f"(d[9]), "+f"(d[10]), "+f"(d[11]), "+f"(d[12]), "+f"(d[13]), "+f"(d[14]), "+f"(d[15]), "+f"(d[16]), "+f"(d[17]), "+f"(d[18]), "+f"(d[19]), "+f"(d[20]), "+f"(d[21]), "+f"(d[22]), "+f"(d[23]), "+f"(d[24]), "+f"(d[25]), "+f"(d[26]), "+f"(d[27]), "+f"(d[28]), "+f"(d[29]), "+f"(d[30]), "+f"(d[31]), "+f"(d[32]), "+f"(d[33]), "+f"(d[34]), "+f"(d[35]), "+f"(d[36]), "+f"(d[37]), "+f"(d[38]), "+f"(d[39]), "+f"(d[40]), "+f"(d[41]), "+f"(d[42]), "+f"(d[43]), "+f"(d[44]), "+f"(d[45]), "+f"(d[46]), "+f"(d[47]), "+f"(d[48]), "+f"(d[49]), "+f"(d[50]), "+f"(d[51]), "+f"(d[52]), "+f"(d[53]), "+f"(d[54]), "+f"(d[55]), "+f"(d[56]), "+f"(d[57]), "+f"(d[58]), "+f"(d[59]), "+f"(d[60]), "+f"(d[61]), "+f"(d[62]), "+f"(d[63]), "+f"(d[64]), "+f"(d[65]), "+f"(d[66]), "+f"(d[67]), "+f"(d[68]), "+f"(d[69]), "+f"(d[70]), "+f"(d[71]), "+f"(d[72]), "+f"(d[73]), "+f"(d[74]), "+f"(d[75]), "+f"(d[76]), "+f"(d[77]), "+f"(d[78]), "+f"(d[79]), "+f"(d[80]), "+f"(d[81]), "+f"(d[82]), "+f"(d[83]), "+f"(d[84]), "+f"(d[85]), "+f"(d[86]), "+f"(d[87]), "+f"(d[88]), "+f"(d[89]), "+f"(d[90]), "+f"(d[91]), "+f"(d[92]), "+f"(d[93]), "+f"(d[94]), "+f"(d[95]) : "r"(a[0]), "r"(a[1]), "r"(a[2]), "r"(a[3]), "l"(db));
}
template <> DEV void wgmma_rs<176>(float* d, const u32* a, u64 db) {
  asm volatile("wgmma.mma_async.sync.aligned.m64n176k16.f32.bf16.bf16 {%0, %1, %2, %3, %4, %5, %6, %7, %8, %9, %10, %11, %12, %13, %14, %15, %16, %17, %18, %19, %20, %21, %22, %23, %24, %25, %26, %27, %28, %29, %30, %31, %32, %33, %34, %35, %36, %37, %38, %39, %40, %41, %42, %43, %44, %45, %46, %47, %48, %49, %50, %51, %52, %53, %54, %55, %56, %57, %58, %59, %60, %61, %62, %63, %64, %65, %66, %67, %68, %69, %70, %71, %72, %73, %74, %75, %76, %77, %78, %79, %80, %81, %82, %83, %84, %85, %86, %87}, {%88, %89, %90, %91}, %92, 1, 1, 1, 0;"
    : "+f"(d[0]), "+f"(d[1]), "+f"(d[2]), "+f"(d[3]), "+f"(d[4]), "+f"(d[5]), "+f"(d[6]), "+f"(d[7]), "+f"(d[8]), "+f"(d[9]), "+f"(d[10]), "+f"(d[11]), "+f"(d[12]), "+f"(d[13]), "+f"(d[14]), "+f"(d[15]), "+f"(d[16]), "+f"(d[17]), "+f"(d[18]), "+f"(d[19]), "+f"(d[20]), "+f"(d[21]), "+f"(d[22]), "+f"(d[23]), "+f"(d[24]), "+f"(d[25]), "+f"(d[26]), "+f"(d[27]), "+f"(d[28]), "+f"(d[29]), "+f"(d[30]), "+f"(d[31]), "+f"(d[32]), "+f"(d[33]), "+f"(d[34]), "+f"(d[35]), "+f"(d[36]), "+f"(d[37]), "+f"(d[38]), "+f"(d[39]), "+f"(d[40]), "+f"(d[41]), "+f"(d[42]), "+f"(d[43]), "+f"(d[44]), "+f"(d[45]), "+f"(d[46]), "+f"(d[47]), "+f"(d[48]), "+f"(d[49]), "+f"(d[50]), "+f"(d[51]), "+f"(d[52]), "+f"(d[53]), "+f"(d[54]), "+f"(d[55]), "+f"(d[56]), "+f"(d[57]), "+f"(d[58]), "+f"(d[59]), "+f"(d[60]), "+f"(d[61]), "+f"(d[62]), "+f"(d[63]), "+f"(d[64]), "+f"(d[65]), "+f"(d[66]), "+f"(d[67]), "+f"(d[68]), "+f"(d[69]), "+f"(d[70]), "+f"(d[71]), "+f"(d[72]), "+f"(d[73]), "+f"(d[74]), "+f"(d[75]), "+f"(d[76]), "+f"(d[77]), "+f"(d[78]), "+f"(d[79]), "+f"(d[80]), "+f"(d[81]), "+f"(d[82]), "+f"(d[83]), "+f"(d[84]), "+f"(d[85]), "+f"(d[86]), "+f"(d[87]) : "r"(a[0]), "r"(a[1]), "r"(a[2]), "r"(a[3]), "l"(db));
}
template <> DEV void wgmma_rs<160>(float* d, const u32* a, u64 db) {
  asm volatile("wgmma.mma_async.sync.aligned.m64n160k16.f32.bf16.bf16 {%0, %1, %2, %3, %4, %5, %6, %7, %8, %9, %10, %11, %12, %13, %14, %15, %16, %17, %18, %19, %20, %21, %22, %23, %24, %25, %26, %27, %28, %29, %30, %31, %32, %33, %34, %35, %36, %37, %38, %39, %40, %41, %42, %43, %44, %45, %46, %47, %48, %49, %50, %51, %52, %53, %54, %55, %56, %57, %58, %59, %60, %61, %62, %63, %64, %65, %66, %67, %68, %69, %70, %71, %72, %73, %74, %75, %76, %77, %78, %79}, {%80, %81, %82, %83}, %84, 1, 1, 1, 0;"
    : "+f"(d[0]), "+f"(d[1]), "+f"(d[2]), "+f"(d[3]), "+f"(d[4]), "+f"(d[5]), "+f"(d[6]), "+f"(d[7]), "+f"(d[8]), "+f"(d[9]), "+f"(d[10]), "+f"(d[11]), "+f"(d[12]), "+f"(d[13]), "+f"(d[14]), "+f"(d[15]), "+f"(d[16]), "+f"(d[17]), "+f"(d[18]), "+f"(d[19]), "+f"(d[20]), "+f"(d[21]), "+f"(d[22]), "+f"(d[23]), "+f"(d[24]), "+f"(d[25]), "+f"(d[26]), "+f"(d[27]), "+f"(d[28]), "+f"(d[29]), "+f"(d[30]), "+f"(d[31]), "+f"(d[32]), "+f"(d[33]), "+f"(d[34]), "+f"(d[35]), "+f"(d[36]), "+f"(d[37]), "+f"(d[38]), "+f"(d[39]), "+f"(d[40]), "+f"(d[41]), "+f"(d[42]), "+f"(d[43]), "+f"(d[44]), "+f"(d[45]), "+f"(d[46]), "+f"(d[47]), "+f"(d[48]), "+f"(d[49]), "+f"(d[50]), "+f"(d[51]), "+f"(d[52]), "+f"(d[53]), "+f"(d[54]), "+f"(d[55]), "+f"(d[56]), "+f"(d[57]), "+f"(d[58]), "+f"(d[59]), "+f"(d[60]), "+f"(d[61]), "+f"(d[62]), "+f"(d[63]), "+f"(d[64]), "+f"(d[65]), "+f"(d[66]), "+f"(d[67]), "+f"(d[68]), "+f"(d[69]), "+f"(d[70]), "+f"(d[71]), "+f"(d[72]), "+f"(d[73]), "+f"(d[74]), "+f"(d[75]), "+f"(d[76]), "+f"(d[77]), "+f"(d[78]), "+f"(d[79]) : "r"(a[0]), "r"(a[1]), "r"(a[2]), "r"(a[3]), "l"(db));
}
template <> DEV void wgmma_rs<144>(float* d, const u32* a, u64 db) {
  asm volatile("wgmma.mma_async.sync.aligned.m64n144k16.f32.bf16.bf16 {%0, %1, %2, %3, %4, %5, %6, %7, %8, %9, %10, %11, %12, %13, %14, %15, %16, %17, %18, %19, %20, %21, %22, %23, %24, %25, %26, %27, %28, %29, %30, %31, %32, %33, %34, %35, %36, %37, %38, %39, %40, %41, %42, %43, %44, %45, %46, %47, %48, %49, %50, %51, %52, %53, %54, %55, %56, %57, %58, %59, %60, %61, %62, %63, %64, %65, %66, %67, %68, %69, %70, %71}, {%72, %73, %74, %75}, %76, 1, 1, 1, 0;"
    : "+f"(d[0]), "+f"(d[1]), "+f"(d[2]), "+f"(d[3]), "+f"(d[4]), "+f"(d[5]), "+f"(d[6]), "+f"(d[7]), "+f"(d[8]), "+f"(d[9]), "+f"(d[10]), "+f"(d[11]), "+f"(d[12]), "+f"(d[13]), "+f"(d[14]), "+f"(d[15]), "+f"(d[16]), "+f"(d[17]), "+f"(d[18]), "+f"(d[19]), "+f"(d[20]), "+f"(d[21]), "+f"(d[22]), "+f"(d[23]), "+f"(d[24]), "+f"(d[25]), "+f"(d[26]), "+f"(d[27]), "+f"(d[28]), "+f"(d[29]), "+f"(d[30]), "+f"(d[31]), "+f"(d[32]), "+f"(d[33]), "+f"(d[34]), "+f"(d[35]), "+f"(d[36]), "+f"(d[37]), "+f"(d[38]), "+f"(d[39]), "+f"(d[40]), "+f"(d[41]), "+f"(d[42]), "+f"(d[43]), "+f"(d[44]), "+f"(d[45]), "+f"(d[46]), "+f"(d[47]), "+f"(d[48]), "+f"(d[49]), "+f"(d[50]), "+f"(d[51]), "+f"(d[52]), "+f"(d[53]), "+f"(d[54]), "+f"(d[55]), "+f"(d[56]), "+f"(d[57]), "+f"(d[58]), "+f"(d[59]), "+f"(d[60]), "+f"(d[61]), "+f"(d[62]), "+f"(d[63]), "+f"(d[64]), "+f"(d[65]), "+f"(d[66]), "+f"(d[67]), "+f"(d[68]), "+f"(d[69]), "+f"(d[70]), "+f"(d[71]) : "r"(a[0]), "r"(a[1]), "r"(a[2]), "r"(a[3]), "l"(db));
}
template <> DEV void wgmma_rs<128>(float* d, const u32* a, u64 db) {
  asm volatile("wgmma.mma_async.sync.aligned.m64n128k16.f32.bf16.bf16 {%0, %1, %2, %3, %4, %5, %6, %7, %8, %9, %10, %11, %12, %13, %14, %15, %16, %17, %18, %19, %20, %21, %22, %23, %24, %25, %26, %27, %28, %29, %30, %31, %32, %33, %34, %35, %36, %37, %38, %39, %40, %41, %42, %43, %44, %45, %46, %47, %48, %49, %50, %51, %52, %53, %54, %55, %56, %57, %58, %59, %60, %61, %62, %63}, {%64, %65, %66, %67}, %68, 1, 1, 1, 0;"
    : "+f"(d[0]), "+f"(d[1]), "+f"(d[2]), "+f"(d[3]), "+f"(d[4]), "+f"(d[5]), "+f"(d[6]), "+f"(d[7]), "+f"(d[8]), "+f"(d[9]), "+f"(d[10]), "+f"(d[11]), "+f"(d[12]), "+f"(d[13]), "+f"(d[14]), "+f"(d[15]), "+f"(d[16]), "+f"(d[17]), "+f"(d[18]), "+f"(d[19]), "+f"(d[20]), "+f"(d[21]), "+f"(d[22]), "+f"(d[23]), "+f"(d[24]), "+f"(d[25]), "+f"(d[26]), "+f"(d[27]), "+f"(d[28]), "+f"(d[29]), "+f"(d[30]), "+f"(d[31]), "+f"(d[32]), "+f"(d[33]), "+f"(d[34]), "+f"(d[35]), "+f"(d[36]), "+f"(d[37]), "+f"(d[38]), "+f"(d[39]), "+f"(d[40]), "+f"(d[41]), "+f"(d[42]), "+f"(d[43]), "+f"(d[44]), "+f"(d[45]), "+f"(d[46]), "+f"(d[47]), "+f"(d[48]), "+f"(d[49]), "+f"(d[50]), "+f"(d[51]), "+f"(d[52]), "+f"(d[53]), "+f"(d[54]), "+f"(d[55]), "+f"(d[56]), "+f"(d[57]), "+f"(d[58]), "+f"(d[59]), "+f"(d[60]), "+f"(d[61]), "+f"(d[62]), "+f"(d[63]) : "r"(a[0]), "r"(a[1]), "r"(a[2]), "r"(a[3]), "l"(db));
}
template <> DEV void wgmma_rs<112>(float* d, const u32* a, u64 db) {
  asm volatile("wgmma.mma_async.sync.aligned.m64n112k16.f32.bf16.bf16 {%0, %1, %2, %3, %4, %5, %6, %7, %8, %9, %10, %11, %12, %13, %14, %15, %16, %17, %18, %19, %20, %21, %22, %23, %24, %25, %26, %27, %28, %29, %30, %31, %32, %33, %34, %35, %36, %37, %38, %39, %40, %41, %42, %43, %44, %45, %46, %47, %48, %49, %50, %51, %52, %53, %54, %55}, {%56, %57, %58, %59}, %60, 1, 1, 1, 0;"
    : "+f"(d[0]), "+f"(d[1]), "+f"(d[2]), "+f"(d[3]), "+f"(d[4]), "+f"(d[5]), "+f"(d[6]), "+f"(d[7]), "+f"(d[8]), "+f"(d[9]), "+f"(d[10]), "+f"(d[11]), "+f"(d[12]), "+f"(d[13]), "+f"(d[14]), "+f"(d[15]), "+f"(d[16]), "+f"(d[17]), "+f"(d[18]), "+f"(d[19]), "+f"(d[20]), "+f"(d[21]), "+f"(d[22]), "+f"(d[23]), "+f"(d[24]), "+f"(d[25]), "+f"(d[26]), "+f"(d[27]), "+f"(d[28]), "+f"(d[29]), "+f"(d[30]), "+f"(d[31]), "+f"(d[32]), "+f"(d[33]), "+f"(d[34]), "+f"(d[35]), "+f"(d[36]), "+f"(d[37]), "+f"(d[38]), "+f"(d[39]), "+f"(d[40]), "+f"(d[41]), "+f"(d[42]), "+f"(d[43]), "+f"(d[44]), "+f"(d[45]), "+f"(d[46]), "+f"(d[47]), "+f"(d[48]), "+f"(d[49]), "+f"(d[50]), "+f"(d[51]), "+f"(d[52]), "+f"(d[53]), "+f"(d[54]), "+f"(d[55]) : "r"(a[0]), "r"(a[1]), "r"(a[2]), "r"(a[3]), "l"(db));
}
template <> DEV void wgmma_rs<96>(float* d, const u32* a, u64 db) {
  asm volatile("wgmma.mma_async.sync.aligned.m64n96k16.f32.bf16.bf16 {%0, %1, %2, %3, %4, %5, %6, %7, %8, %9, %10, %11, %12, %13, %14, %15, %16, %17, %18, %19, %20, %21, %22, %23, %24, %25, %26, %27, %28, %29, %30, %31, %32, %33, %34, %35, %36, %37, %38, %39, %40, %41, %42, %43, %44, %45, %46, %47}, {%48, %49, %50, %51}, %52, 1, 1, 1, 0;"
    : "+f"(d[0]), "+f"(d[1]), "+f"(d[2]), "+f"(d[3]), "+f"(d[4]), "+f"(d[5]), "+f"(d[6]), "+f"(d[7]), "+f"(d[8]), "+f"(d[9]), "+f"(d[10]), "+f"(d[11]), "+f"(d[12]), "+f"(d[13]), "+f"(d[14]), "+f"(d[15]), "+f"(d[16]), "+f"(d[17]), "+f"(d[18]), "+f"(d[19]), "+f"(d[20]), "+f"(d[21]), "+f"(d[22]), "+f"(d[23]), "+f"(d[24]), "+f"(d[25]), "+f"(d[26]), "+f"(d[27]), "+f"(d[28]), "+f"(d[29]), "+f"(d[30]), "+f"(d[31]), "+f"(d[32]), "+f"(d[33]), "+f"(d[34]), "+f"(d[35]), "+f"(d[36]), "+f"(d[37]), "+f"(d[38]), "+f"(d[39]), "+f"(d[40]), "+f"(d[41]), "+f"(d[42]), "+f"(d[43]), "+f"(d[44]), "+f"(d[45]), "+f"(d[46]), "+f"(d[47]) : "r"(a[0]), "r"(a[1]), "r"(a[2]), "r"(a[3]), "l"(db));
}
template <> DEV void wgmma_rs<80>(float* d, const u32* a, u64 db) {
  asm volatile("wgmma.mma_async.sync.aligned.m64n80k16.f32.bf16.bf16 {%0, %1, %2, %3, %4, %5, %6, %7, %8, %9, %10, %11, %12, %13, %14, %15, %16, %17, %18, %19, %20, %21, %22, %23, %24, %25, %26, %27, %28, %29, %30, %31, %32, %33, %34, %35, %36, %37, %38, %39}, {%40, %41, %42, %43}, %44, 1, 1, 1, 0;"
    : "+f"(d[0]), "+f"(d[1]), "+f"(d[2]), "+f"(d[3]), "+f"(d[4]), "+f"(d[5]), "+f"(d[6]), "+f"(d[7]), "+f"(d[8]), "+f"(d[9]), "+f"(d[10]), "+f"(d[11]), "+f"(d[12]), "+f"(d[13]), "+f"(d[14]), "+f"(d[15]), "+f"(d[16]), "+f"(d[17]), "+f"(d[18]), "+f"(d[19]), "+f"(d[20]), "+f"(d[21]), "+f"(d[22]), "+f"(d[23]), "+f"(d[24]), "+f"(d[25]), "+f"(d[26]), "+f"(d[27]), "+f"(d[28]), "+f"(d[29]), "+f"(d[30]), "+f"(d[31]), "+f"(d[32]), "+f"(d[33]), "+f"(d[34]), "+f"(d[35]), "+f"(d[36]), "+f"(d[37]), "+f"(d[38]), "+f"(d[39]) : "r"(a[0]), "r"(a[1]), "r"(a[2]), "r"(a[3]), "l"(db));
}
template <> DEV void wgmma_rs<64>(float* d, const u32* a, u64 db) {
  asm volatile("wgmma.mma_async.sync.aligned.m64n64k16.f32.bf16.bf16 {%0, %1, %2, %3, %4, %5, %6, %7, %8, %9, %10, %11, %12, %13, %14, %15, %16, %17, %18, %19, %20, %21, %22, %23, %24, %25, %26, %27, %28, %29, %30, %31}, {%32, %33, %34, %35}, %36, 1, 1, 1, 0;"
    : "+f"(d[0]), "+f"(d[1]), "+f"(d[2]), "+f"(d[3]), "+f"(d[4]), "+f"(d[5]), "+f"(d[6]), "+f"(d[7]), "+f"(d[8]), "+f"(d[9]), "+f"(d[10]), "+f"(d[11]), "+f"(d[12]), "+f"(d[13]), "+f"(d[14]), "+f"(d[15]), "+f"(d[16]), "+f"(d[17]), "+f"(d[18]), "+f"(d[19]), "+f"(d[20]), "+f"(d[21]), "+f"(d[22]), "+f"(d[23]), "+f"(d[24]), "+f"(d[25]), "+f"(d[26]), "+f"(d[27]), "+f"(d[28]), "+f"(d[29]), "+f"(d[30]), "+f"(d[31]) : "r"(a[0]), "r"(a[1]), "r"(a[2]), "r"(a[3]), "l"(db));
}
template <> DEV void wgmma_rs<48>(float* d, const u32* a, u64 db) {
  asm volatile("wgmma.mma_async.sync.aligned.m64n48k16.f32.bf16.bf16 {%0, %1, %2, %3, %4, %5, %6, %7, %8, %9, %10, %11, %12, %13, %14, %15, %16, %17, %18, %19, %20, %21, %22, %23}, {%24, %25, %26, %27}, %28, 1, 1, 1, 0;"
    : "+f"(d[0]), "+f"(d[1]), "+f"(d[2]), "+f"(d[3]), "+f"(d[4]), "+f"(d[5]), "+f"(d[6]), "+f"(d[7]), "+f"(d[8]), "+f"(d[9]), "+f"(d[10]), "+f"(d[11]), "+f"(d[12]), "+f"(d[13]), "+f"(d[14]), "+f"(d[15]), "+f"(d[16]), "+f"(d[17]), "+f"(d[18]), "+f"(d[19]), "+f"(d[20]), "+f"(d[21]), "+f"(d[22]), "+f"(d[23]) : "r"(a[0]), "r"(a[1]), "r"(a[2]), "r"(a[3]), "l"(db));
}
template <> DEV void wgmma_rs<32>(float* d, const u32* a, u64 db) {
  asm volatile("wgmma.mma_async.sync.aligned.m64n32k16.f32.bf16.bf16 {%0, %1, %2, %3, %4, %5, %6, %7, %8, %9, %10, %11, %12, %13, %14, %15}, {%16, %17, %18, %19}, %20, 1, 1, 1, 0;"
    : "+f"(d[0]), "+f"(d[1]), "+f"(d[2]), "+f"(d[3]), "+f"(d[4]), "+f"(d[5]), "+f"(d[6]), "+f"(d[7]), "+f"(d[8]), "+f"(d[9]), "+f"(d[10]), "+f"(d[11]), "+f"(d[12]), "+f"(d[13]), "+f"(d[14]), "+f"(d[15]) : "r"(a[0]), "r"(a[1]), "r"(a[2]), "r"(a[3]), "l"(db));
}
template <> DEV void wgmma_rs<16>(float* d, const u32* a, u64 db) {
  asm volatile("wgmma.mma_async.sync.aligned.m64n16k16.f32.bf16.bf16 {%0, %1, %2, %3, %4, %5, %6, %7}, {%8, %9, %10, %11}, %12, 1, 1, 1, 0;"
    : "+f"(d[0]), "+f"(d[1]), "+f"(d[2]), "+f"(d[3]), "+f"(d[4]), "+f"(d[5]), "+f"(d[6]), "+f"(d[7]) : "r"(a[0]), "r"(a[1]), "r"(a[2]), "r"(a[3]), "l"(db));
}

#define T_G 390
#define T_0 300
#define T_G2 300
#define ORDER (H4 ? 0xedcb8a957643210ull : 0xeb8dca957643210ull)
#define T_U0 5000
#define T_U1 4650
#define T_UP 1200
#define D_U 800
#define D_Y 2200
#define D_M 2100
#define D_H 1100
#define G_H 500
#define T_W 12000
#define G_W 500
#define R0 3
#define PROF0 0
#define SWAPWG 0
#define PROMO 2
#define T_X 0
#define T_PF 400
#define T_ZS 100
#define T_P 2250
#define T_P2 3700
#define D_Z 9700
#ifndef NV
#define NV 3
#endif
#define T_WO 3000
#define KT 31
#define NR0 4
#define NR1 4
#define NH 4
#define WL 2
#define KP2 28
#define NPE 8
#define T_R 3100
#define G_R 250
#define G_P 40
#define H4 0
#define RND0 0xf20
#define RND1 (H4 ? 0xf31 : 0xf431)
#define KX0 8
#define KX1 5
#define SPF 1
#define SPD 0
#define YG 3
#define D_Y3 1500
#define D_HG 0
#define G_S 280
#define G_S0 620
#define NP0 2
#define NP1 2
#define KZ0 2
#define KZ1 4
#define DKZ 2

template <int NW> DEV void phase_a(const Params& p, int j, int q, int role, int lane, u32 par) {
  const int o = lane & 3, cl = (8 * q + (lane >> 2)) * 2 * NW, c = 128 * j + 64 * (role & 1) + cl;
  const u32 ka = sb + j * KVP + o * 1024 + cl * 2;
  u32 sw[NW][4], k[11][NW], r[8][NW];
#pragma unroll
  for (int e = 0; e < NW; e++) lds128(sw[e], sb + SHK + c * 8 + e * 16);
#pragma unroll
  for (int i = 0; i < 11; i++) { if (NW == 2) lds64(k[i], ka + i * 128); else k[i][0] = lds32(ka + i * 128); }
#pragma unroll
  for (int i = 0; i < 8; i++) { if (NW == 2) lds64(r[i], ka + VO + i * 128); else r[i][0] = lds32(ka + VO + i * 128); }
  u16* dst = p.s->u + c * 2048 + 2040 - 32 * (role >> 1) - 8 * o;
#pragma unroll
  for (int e = 0; e < NW; e++) {
    const u32 w0 = prmt(sw[e][0], sw[e][2], 0x5410), w1 = prmt(sw[e][0], sw[e][2], 0x7632), w2 = prmt(sw[e][1], sw[e][3], 0x5410), w3 = prmt(sw[e][1], sw[e][3], 0x7632);
#pragma unroll
    for (int i = 0; i < 8; i++) r[i][e] = hmul2(hfma2(k[i + 3][e], w0, hfma2(k[i + 2][e], w1, hfma2(k[i + 1][e], w2, hmul2(k[i][e], w3)))), r[i][e]);
    r[7][e] = tagw(r[7][e], (o & 1) * 0x10001u, par);
    stg128(dst + e * 4096, make_uint4(prmt(r[7][e], r[6][e], 0x5410), prmt(r[5][e], r[4][e], 0x5410), prmt(r[3][e], r[2][e], 0x5410), prmt(r[1][e], r[0][e], 0x5410)));
    stg128(dst + e * 4096 + 2048, make_uint4(prmt(r[7][e], r[6][e], 0x7632), prmt(r[5][e], r[4][e], 0x7632), prmt(r[3][e], r[2][e], 0x7632), prmt(r[1][e], r[0][e], 0x7632)));
  }
}
template <int N, int STRIDE> DEV void shift_copy(u32 a, u32 dv, bool first) {
  uint4 w[N]; u32 pv[N];
#pragma unroll
  for (int i = 0; i < N; i++) { w[i] = lds128(a + i * STRIDE); pv[i] = lds32(a + i * STRIDE - 4); }
  if (first) { w[0].x = hadd2(w[0].x, dv); sts32(a, w[0].x); }
#pragma unroll
  for (int i = 0; i < N; i++)
    sts128(a + KO + i * STRIDE, make_uint4(prmt(pv[i], w[i].x, 0x5432), prmt(w[i].x, w[i].y, 0x5432), prmt(w[i].y, w[i].z, 0x5432), prmt(w[i].z, w[i].w, 0x5432)));
}
template <int S0, int S1> DEV void load_a(u32* a, u32 p) {
#pragma unroll
  for (int s = S0; s < S1; s++) { a[4 * s] = lds32(p + 256 * s); a[4 * s + 1] = lds32(p + 256 * s + 128); a[4 * s + 2] = lds32(p + 256 * s + 16); a[4 * s + 3] = lds32(p + 256 * s + 144); }
}
template <int S> DEV void load_a_if(u32* a, u32 p, bool c) {
  asm volatile("{\n.reg .pred q;\nsetp.ne.u32 q, %5, 0;\n@q ld.shared.b32 %0, [%4+%6];\n@q ld.shared.b32 %1, [%4+%7];\n@q ld.shared.b32 %2, [%4+%8];\n@q ld.shared.b32 %3, [%4+%9];\n}\n"
               : "+r"(a[4 * S]), "+r"(a[4 * S + 1]), "+r"(a[4 * S + 2]), "+r"(a[4 * S + 3])
               : "r"(p), "r"((u32)c), "n"(256 * S), "n"(256 * S + 128), "n"(256 * S + 16), "n"(256 * S + 144) : "memory");
}
template <int K> DEV void conv_pair(float* d, const u32* a, u32 lo) {
  wgmma_rs<256 - 32 * K>(d, a + 8 * K, desc_join(lo + 32 * K, 8u));
  wgmma_rs<240 - 32 * K>(d, a + 8 * K + 4, desc_join(lo + 32 * K + 16, 8u));
  wg_commit();
}
template <int K> DEV void conv_work(const float* d, u32* a, u32 ps, u32 pn, bool more) {
  constexpr int I = 7 - K;
  u32 pk[4];
  if constexpr (K >= R0) load_a_if<2 * (K - R0)>(a, pn, more);
#pragma unroll
  for (int e = 0; e < 4; e++) {
    const int nb = 4 * I + e;
    pk[e] = nb < 31 ? pack2(d[4 * nb] + d[(4 * nb + 6) & 127], d[4 * nb + 1] + d[(4 * nb + 7) & 127]) : pack2(d[4 * nb], d[4 * nb + 1]);
  }
  stsm4t(ps - 512 * I, pk);
  if constexpr (K >= R0) load_a_if<2 * (K - R0) + 1>(a, pn, more);
}
template <int NB> DEV int validate(u32 bf, u32 par, u32 dst, u32 off, u32 old, u32 done, const void* src, u32 rbar, u32& rph) {
  int n = 0;
  const u32 a = opaque(dst + off);
  mbar_wait(bf, par);
  PROF(threadIdx.x == (NB == 8 ? 320 : 288) && (NB > 9 || done == bar(B_VAL) || done == bar(B_ZV)), NB == 8 ? 61 : NB == 9 ? 117 : 122 + (NB > 11));
#pragma unroll 1
  while (true) {
    u32 v[NB], m = 1;
#pragma unroll
    for (int i = 0; i < NB; i++) v[i] = lds32(a + i * 1024);
#pragma unroll
    for (int i = 0; i < NB; i++) asm("lop3.b32 %0, %0, %1, %2, 0x60;" : "+r"(m) : "r"(v[i]), "r"(old));
    const bool ok = __all_sync(0xffffffffu, m);
    mbar_arrive_if(done, ok && off == 0);
    if (ok) break;
    trap_if_gt(++n, 1 << 16);
    RST(NB);
    e_xload(dst, src, NB * 1024, rbar);
    mbar_wait(rbar, rph);
    rph ^= 1;
  }
  return n;
}
DEV void ln_post(float (*c)[4], u32 a, int lane) {
  const bool o = lane & 4;
  if ((lane & 3) == (lane >> 3)) sts128(a, make_uint4(__float_as_uint(c[0][0]), __float_as_uint(o ? c[1][1] : c[1][0]), __float_as_uint(c[0][2]), __float_as_uint(o ? c[2][3] : c[2][2])));
}
template <int NW> DEV void ln_params(u32 a, u32* r2, u32* n2) {
  u32 v[8][4];
#pragma unroll
  for (int i = 0; i < NW; i++) lds128(v[i], a + i * 128);
#pragma unroll
  for (int hh = 0; hh < 2; hh++) {
    auto sum4 = [&](int i, int e) { return (__uint_as_float(v[i][e]) + __uint_as_float(v[i + 1][e])) + (__uint_as_float(v[i + 2][e]) + __uint_as_float(v[i + 3][e])); };
    auto sum = [&](int e) { return NW == 8 ? sum4(0, e) + sum4(4, e) : sum4(0, e); };
    const float mu = sum(2 * hh) * (1.f / 640.f), rs = rsq(fmaxf(sum(2 * hh + 1) * (1.f / 640.f) - mu * mu, 0.f) + 1e-5f);
    r2[hh] = pack2(rs, rs);
    const float nm = NW == 8 ? -mu * bfhi(r2[hh]) : -mu;
    n2[hh] = pack2(nm, nm);
  }
}
DEV void fetch_y(const Maps& tm, int j0, int j1, int role) {
  e_expect(bar(B_YF + (j0 > 0)), 4096 * (j1 - j0));
#pragma unroll 1
  for (int j = j0; j < j1; j++) e_tma2d(sb + YS + j * 4096, &tm.y, bar(B_YF + (j0 > 0)), 16 * (role & 3), (role >> 2) * 640 + 128 * j);
}
DEV float gelu2(float a) { return fmaf(a, tanh_fast(a * fmaf(0.035677408136300125f, a * a, 0.7978845608028654f)), a); }

template <int N>
DEV void g1_pass(float* acc, u32* zp, const u32* x1, int pass, int t128, u32* z2p, u32* hp, u32 ep) {
  constexpr int NG = N / 8, WG = N == 88, NPART = WG ? NP1 : NP0, PART = (NG + NPART - 1) / NPART, K0 = WG ? KZ1 : KZ0;
  constexpr u32 LB0 = WG ? desc_lo(sb + 16384, 1408) : desc_lo(sb, 8192), SIDE = (NPART == 2 ? 1 + (1 << DKZ) : 1) << K0;
  const int lane = t128 & 31;
  const u32 stop = pass ? 512 + SIDE : 512 + (WG ? (KX1 < 0 ? 0 : 1 << KX1) : 1 << KX0) + (NH < 5);
  auto put_x1 = [&]() {
    u32* xp = (u32*)((size_t)hp ^ ((t128 & 32) << 1)) + 32 * 80 * 8 * 32;
#pragma unroll
    for (int i = 0; i < 20; i++) stg32((u32*)((size_t)xp ^ ((i & 2) << 4)) + (16 * (i >> 2) + ((i >> 1) & 1)) * 256 + (i & 1) * 32, x1[i]);
  };
  if (WG && KX1 == -1 && pass == 0) put_x1();
  u32 la = desc_lo(sb + XR, 1024), lb = LB0, bf = bar(B_FULL), bv = bar(B_VAL), par = 0, bprev = bar(B_DUMMY), kb = 0;
#pragma unroll 1
  do {
#pragma unroll 1
    do {
      mbar_wait(bv & ~7u, 0);
      mbar_wait(bf, par);
      PROF(kb == 0 && t128 == 0, WG ? 109 + pass : 40 + pass);
      wg_fence();
#pragma unroll
      for (int q = 0; q < 4; q++) {
        if constexpr (WG) wgmma_ss_88(acc, desc_join(la + q * 128, 8u), desc_join(lb + q * 176, 8u), kb | q);
        else wgmma_ss_128(acc, desc_join(la + q * 128, 8u), desc_join(lb + q * 128, 0x40000040u), kb | q);
      }
      wg_commit();
      const u32 bcur = bf + 8 * (B_EMPTY - B_FULL);
      kb = max(2 * kb, 1u);
      const bool wrap = kb == 16;
      par ^= wrap; bf = wrap ? bar(B_FULL) : bf + 8; bv += 4;
      la += 512; lb = wrap ? LB0 : lb + (BT >> 4);
      wg_wait<1>();
      mbar_arrive_if(bprev, t128 == 0);
      bprev = bcur;
    } while (!(kb & stop));
    if (kb != 512) {
      const int c = (lane + 2 * (t128 >> 5)) & 7;
      auto put = [&](int pt) {
#pragma unroll
        for (int n = pt * PART; n < (pt + 1) * PART && n < NG; n++) {
          const int gq = N == 128 ? 4 + n : n < 4 ? n : 16 + n;
          stg32(z2p + gq * 32, tagw(zp[2 * n], c == (gq & 7), ~ep));
          stg32(z2p + (27 + gq) * 32, tagw(zp[2 * n + 1], c == ((gq + 3) & 7), ~ep));
        }
        if (pt == NPART - 1) { __syncwarp(); mbar_arrive_if(bar(B_Z2D), lane == 0); PROF(t128 == 0, 107 + WG); }
      };
      if (NH < 5 && kb == 1) {
#pragma unroll
        for (int i = 4 * NH; i < 20; i++) stg32(hp + (16 * (i >> 2) + ((i >> 1) & 1)) * 256 + (i & 1) * 32, zp[i]);
      } else if ((!WG || KX1 >= 0) && pass == 0) put_x1();
      else if (kb == 1 << K0) {
        mbar_wait(bar(B_ZS), 0);
        PROF(t128 == 0, WG ? 47 : 106);
        const u32 zsp = sb + M_ZS + (t128 >> 5) * 64 + (lane & 28), v0 = lds32(zsp), v1 = lds32(zsp + 32);
        const u32 r0 = prmt(v0, v0, 0x1010), n0 = prmt(v0, v0, 0x3232), r1 = prmt(v1, v1, 0x1010), n1 = prmt(v1, v1, 0x3232);
#pragma unroll
        for (int n = 0; n < NG; n++) { zp[2 * n] = hfma2(zp[2 * n], r0, n0); zp[2 * n + 1] = hfma2(zp[2 * n + 1], r1, n1); }
        put(0);
      } else if (NPART == 2) put(1);
    }
  } while (kb != 512);
  wg_wait<0>();
  mbar_arrive_if(bprev, t128 == 0);
  PK(t128 == 0, WG ? 111 + pass : 43 + pass);
  if (WG && KX1 == -2 && pass == 0) put_x1();
}
template <int N>
DEV void g2_pass(float* acc, bool elect) {
  constexpr u32 ha = 0x40000040u, hb = 8;
  u32 s = 5, la = desc_lo(sb + AR, 16), lb = desc_lo(sb + 5 * BT + (N == 128 ? 0 : 2048), 3456), bf = bar(B_FULL + 5), bv = bar(B_ZV), par = 0, bprev = bar(B_DUMMY), k = 0;
#pragma unroll 1
  do {
    if (N == 128 && k == KP2) { wg_wait<0>(); mbar_arrive_if(bprev, elect); bprev = bar(B_DUMMY); bsync(3, 256); }
    mbar_wait(bv, 0);
    mbar_wait(bf, par);
    PROF(k == 0 && elect, N == 88 ? 121 : 42);
    wg_fence();
#pragma unroll
    for (int q = 0; q < 4; q++) {
      if constexpr (N == 128) wgmma_ss_128(acc, desc_join(la + q * 2, ha), desc_join(lb + q * 432, hb), k | q);
      else wgmma_ss_88(acc, desc_join(la + q * 2, ha), desc_join(lb + q * 432, hb), k | q);
    }
    wg_commit();
    const u32 inc = s == 5 ? -5 : 1, bcur = bf + 8 * (B_EMPTY - B_FULL);
    par ^= s == 4; bf += 8 * inc; bv = min(bv + 8, bar(B_ZV + NV - 1)); k++;
    la += s == 4 ? -5 * 512 : 512; lb += inc * (BT >> 4); s += inc;
    if (N == 88 && k == KT) barrive(3, 256);
    wg_wait<1>();
    mbar_arrive_if(bprev, elect);
    bprev = bcur;
  } while (k < 32);
  if (N == 128) { barrive(4, 256); bsync(7, 256); }
  wg_wait<0>();
  if (N == 88) barrive(7, 256);
}

DEV void spare_cta(const Params& p, const Maps& tm, int cq, int tid, int warp) {
  const int lane = tid & 31, kr = lane & 7, lg = lane >> 3, seg = warp % 3, kq = warp / 3;
  const u32 br = sb + M_BAR;
  e_init(br + 8 * warp, 1); e_init(br + 96 + 8 * warp, 1);
  const u32 ep = ld_rlx32(p.s->ctr);
  __syncthreads();
#define SPROF(i)
  until(clock(), SPD);
  auto release = [&](int f) {
    __syncthreads();
    if (tid == 0) { fence_gpu(); ctr_arrive(p.s->ctr, f, ep, tid); }
    SPROF(10 + f);
    __syncthreads();
  };
  const int ro = (cq & 1) * 3 + (cq >> 1) * 2 + lg, bx = seg < 2 ? seg : 2 + (ro >> 2), ck = seg < 2 ? lg : ro & 3;
#pragma unroll 1
  for (int pass = 0; pass < 2; pass++) {
    const int c0 = (pass ? 0 : 864) + 192 * cq;
    if (warp == 0) {
#pragma unroll 1
      for (int i = 0; i < 20; i++) {
        if ((i & 3) == 0) e_expect(br + 40 * pass + 2 * i, 32768);
        e_tma2d(sb + i * 8192, &tm.win32, br + 40 * pass + 8 * (i >> 2), (i & 2) ? c0 - 192 * cq + 768 + 32 * ((cq >> 1) + (i & 1)) : c0 + ((i & 1) ? 160 : 128 * pass), 128 * (i >> 2));
      }
    }
#pragma unroll 1
    for (int i = 0; i < 5; i++) {
      mbar_wait(br + 40 * pass + 8 * i, 0);
      SPROF(5 * pass + i);
      if (warp == 1 && SPF == 0) { e_pf3d(&tm.win, c0 + 32 - 32 * pass, 128 * i); e_pf3d(&tm.win, c0 + 32 - 32 * pass, 128 * i + 64); }
      if (seg < 2 || lg < 3) {
        uint4 v[4];
#pragma unroll
        for (int e = 0; e < 4; e++) v[e] = lds128(sb + i * 32768 + bx * 8192 + ((4 * e + kq) * 8 + kr) * 64 + ((ck ^ (kr >> 1)) << 4));
#pragma unroll
        for (int e = 0; e < 4; e++) stg128(p.s->ws + (((pass * 4 + cq) * 80 + 16 * i + 4 * e + kq) * 11 + seg * 4 + lg) * 64 + kr * 8, v[e]);
      }
    }
    if (warp == 1 && SPF == 1)
      for (int i = 0; i < 10; i++) e_pf3d(&tm.win, c0 + 32 - 32 * pass, 64 * i);
    release(I_WS + pass);
  }
  auto fetch = [&](int r) {
    const int c2 = (cq + r) & 3;
    e_expect(br + 96 + 8 * r, 69120);
#pragma unroll 1
    for (int e = 0; e < 9; e++) e_tma2d(sb + (r % 3) * 69120 + e * 7680, &tm.wout, br + 96 + 8 * r, 160 * cq, e < 8 ? 192 * c2 + 24 * e : 768 + 24 * c2);
  };
  if (warp == 0) { fetch(0); fetch(1); fetch(2); }
#pragma unroll 1
  for (int r = 0; r < 4; r++) {
    mbar_wait(br + 96 + 8 * r, 0);
    SPROF(13 + (r >> 1));
#pragma unroll 1
    for (int u = warp * 4 + lg; u < 135; u += 48) {
      const int gm = u / 5, be = u % 5, kg = r == 0 ? (gm < 16 ? gm + 10 : gm < 26 ? gm - 16 : 26) : gm < 16 ? 44 + 16 * r + gm : 11 * r + gm;
      const u32 a = sb + (r % 3) * 69120 + (gm * 8 + kr) * 320 + be * 64;
      const uint4 v0 = lds128(a), v1 = lds128(a + 16), v2 = lds128(a + 32), v3 = lds128(a + 48);
      u16* dst = p.s->wo + (cq * 540 + kg * 5 + be) * 256 + kr * 8;
      stg128(dst, make_uint4(v0.x, v1.x, v2.x, v3.x));
      stg128(dst + 64, make_uint4(v0.y, v1.y, v2.y, v3.y));
      stg128(dst + 128, make_uint4(v0.z, v1.z, v2.z, v3.z));
      stg128(dst + 192, make_uint4(v0.w, v1.w, v2.w, v3.w));
    }
    if (r == 0) { __syncthreads(); if (warp == 0) fetch(3); }
  }
  release(I_WO);
}

__global__ void __launch_bounds__(384, 1) mega_kernel(const __grid_constant__ Params p, const __grid_constant__ Maps tm) {
  extern __shared__ __align__(1024) unsigned char smem_raw[];
  const u32 t_start = clock();
  const int tid = threadIdx.x, warp = __shfl_sync(0xffffffffu, tid >> 5, 0), lane = tid & 31;
  int role;
  {
    u32 sm; asm volatile("mov.u32 %0, %%smid;" : "=r"(sm));
    const u32 x = sm - 64, q = (x * 4682u) >> 16;
    const u32 lo = ((sm + 14) & 14) * 8 + (sm >> 4) * 2, hi = ((x - 14 * q) & 14) * 8 + 8 + 2 * q;
    role = sm >= 124 ? sm - 4 : sm >= 120 ? sm + 8 : (sm < 64 ? lo : hi) + (sm & 1);
    role = __shfl_sync(0xffffffffu, role, 0);
  }
  if (role >= 128) { trap_if_gt(smem_u32(smem_raw) ^ sb, 0); spare_cta(p, tm, role - 128, tid, warp); return; }
  const int rt = role >> 2, cq = role & 3;

  e_init(bar(48 + warp), 2);
  if (warp == 8) {
    e_expect(bar(B_KV), KVP);
    e_tma2d(sb, &tm.k, bar(B_KV), 64 * (role & 1), 32 * (role >> 1) - 3);
    e_tma2d(sb + VO, &tm.v, bar(B_KV), 64 * (role & 1), 32 * (role >> 1));
    e_xload(sb + SHK, p.shk, 5120, bar(B_KV));
    PROF(lane == 0, 0);
  }
  if (warp < 6) e_tmpf(&tm.ssm + warp);
  e_init6(bar(warp), (u32)(0x111111a88882ull >> (4 * warp)) & 15);
  if (warp == 8) { e_expect(bar(B_SS), 4096); e_tma2d(sb + kslot(0), &tm.ssm, bar(B_SS), 0, 8 * role); PROF(lane == 0, 98); }
  if (tid < 63) {
    sts128(sb + (tid < 5 ? US + tid * UP + 4096 : tid < 15 ? kslot((tid - 5) >> 1) - 16 + (tid & 1) * KO : PWB + ((tid - 15) & 7) * PWP + ((tid - 15) >> 3) * 16), make_uint4(0, 0, 0, 0));
    fence_async_smem();
  }
  __syncthreads();

  if (warp < 8) {
    asm volatile("setmaxnreg.inc.sync.aligned.u32 224;");
    u32 dv;
    asm volatile("ld.global.nc.u16 %0, [%1];" : "=r"(dv) : "l"(p.ssmD + (tid & 128) + role));
    u32 ep = ld_rlx32(p.s->ctr);
    const int wg = warp >> 2, w = warp & 3, t128 = tid & 127, g = lane >> 2, t = lane & 3;
    const bool elect = t128 == 0;
    const u32 ts = __shfl_sync(0xffffffffu, t_start, 0);
    PROF(tid == 0, 1);
    {
      const u32 koff = sb + ((g & 1) ? 0 : KO) + 4 * (t + (g >> 1) - 3) + 32 * w;
      const u32 pw = sb + PWB + wg * 4 * PWP;
      u32 a[64];
      ep = __shfl_sync(0xffffffffu, ep, 0);
      consume(dv);
      if (wg) mbar_wait(bar(B_KV), 0);
#pragma unroll 1
      for (u32 js = wg ? RND1 : RND0; js != 15; js >>= 4) {
        const int j = js & 15;
        mbar_wait(bar(B_KV + j), 0);
        PROF(elect, j < 2 ? 2 + j : j == 2 ? 91 : j == 3 ? 126 : 93);
        phase_a<1>(p, j, w, role, lane_now(), (ep & 1) - 1);
        PROF(elect, j < 2 ? 4 + j : j == 2 ? 90 : j == 3 ? 127 : 79);
        if (j < 2) {
          mbar_wait(bar(B_SS + wg), 0);
          shift_copy<2, 2048>(sb + kslot(wg) + t128 * 16, dv, elect);
          bsync(1 + wg, 128);
          load_a<0, 16>(a, koff + kslot(wg));
          PROFD(elect, 6 + wg, a[63]);
        }
      }
#pragma unroll 1
      for (int ch = wg; ch < 5; ch += 2) {
        float d[128];
        const u32 pn = koff + kslot(ch + 2), ps = pw + w * (PWP + 32) + (255 - lane_now()) * 16, lo = desc_lo(sb + US + ch * UP, 16);
        const bool more = ch < 3;
        mbar_wait(bar(B_UV + ch), 0);
        if (ch > 0) bsync(3 + wg, 256);
        if (ch == 4) stamp_post(p.s->ctr, ep, S_Y, ts, lane_now() + w);
        PROF(elect, 8 + ch);
        wg_fence();
        conv_pair<0>(d, a, lo); conv_pair<1>(d, a, lo); conv_pair<2>(d, a, lo);
        if (R0 == 0 && more) mbar_wait(bar(B_KB + ch), 0);
        wg_wait<2>();
        mbar_arrive_if(bar(B_EMPTY) + 8 * (ch == 1 ? w >> 1 : ch - 1), w < ((H4 ? 0x12020 : 0x12040) >> (4 * ch) & 7) && lane_now() == 0);
        conv_work<0>(d, a, ps, pn, more); conv_pair<3>(d, a, lo);
        if (R0 == 1 && more) mbar_wait(bar(B_KB + ch), 0);
        wg_wait<2>(); conv_work<1>(d, a, ps, pn, more); conv_pair<4>(d, a, lo);
        if (R0 == 2 && more) mbar_wait(bar(B_KB + ch), 0);
        wg_wait<2>(); conv_work<2>(d, a, ps, pn, more); conv_pair<5>(d, a, lo); conv_pair<6>(d, a, lo); conv_pair<7>(d, a, lo);
        if (ch < 4) barrive(4 - wg, 256);
        if (R0 == 3 && more) mbar_wait(bar(B_KB + ch), 0);
        wg_wait<2>(); conv_work<3>(d, a, ps, pn, more); conv_work<4>(d, a, ps, pn, more); conv_work<5>(d, a, ps, pn, more);
        wg_wait<0>();
        PROFD(elect, 13 + ch, __float_as_uint(d[0]));
        conv_work<6>(d, a, ps, pn, more); conv_work<7>(d, a, ps, pn, more);
        bsync(1 + wg, 128);
        u32 q[2][4][4];
        const int t128 = 32 * w + lane_now();
#pragma unroll
        for (int h = 0; h < 2; h++)
#pragma unroll
          for (int i = 0; i < 4; i++) lds128(q[h][i], pw + i * PWP + h * 2048 + t128 * 16);
        if (more) load_a<16 - 2 * R0, 16>(a, pn);
        u16* yp = p.s->y + ((t128 >> 3) * 640 + 128 * ch + role) * 64 + ((t128 & 7) << 3);
#pragma unroll
        for (int h = 0; h < 2; h++) {
          u32 y[4];
#pragma unroll
          for (int e = 0; e < 4; e++) y[e] = hadd2(hadd2(q[h][0][e], q[h][1][e]), hadd2(q[h][2][e], q[h][3][e]));
          stg128(yp + h * (16 * 640 * 64), make_uint4(tagw(y[0], ~t128 & 1, ~ep), y[1], y[2], y[3]));
        }
        PROF(elect, 18 + ch);
      }
    }
    u32 zp[32], x1[5][4];
    u32* hp = (u32*)p.s->h2 + ((rt * 80 + 2 * warp) * 8 + 2 * cq) * 32 + lane;
    {
      u32 x[5][4], S[5][2], C[5][2], r2[2], n2[2];
      float c[3][4];
      const u32 xa = sb + QS + wg * 2048 + (lane & 15) * 128 + (((2 * w + (lane >> 4)) ^ (lane & 7)) << 4);
      const u32 ya = sb + YS + (16 * warp + (lane >> 4) * 8 + (lane & 7)) * 32 + ((((lane >> 3) ^ (lane >> 2)) & 1) << 4);
      const u32 ma = sb + M_MOD + 64 * (warp >> 1) + 16 * t + 8 * (warp & 1), la = sb + M_LN + g * 16, par = (ep & 1) - 1;
      auto clear = [&]() {
#pragma unroll
        for (int i = 0; i < 12; i++) c[i >> 2][i & 3] = 0.f;
      };
      mbar_wait(bar(B_Q), 0);
      PK(elect, 23 + wg);
#pragma unroll
      for (int j = 0; j < 5; j++) ldsm4(x[j], xa + j * 4096);
      if (wg) asm volatile("st.global.v2.b32 [%0], {%1,%1};" ::"l"(p.s->stz + role * 128 + t128), "r"(ep) : "memory");
      if (wg) {
        clear();
#pragma unroll
        for (int j = 0; j < 5; j++) ldsm4(x1[j], xa + j * 4096 - 2048);
#pragma unroll
        for (int j = 0; j < 5; j++) { row_stats(c, x[j]); row_stats(c, x1[j]); }
        ln_post(c, la + w * 128, lane);
        bsync(2, 128);
        ln_params<4>(la, r2, n2);
        if (w == 0) sts128(la + 512, make_uint4(r2[0], r2[1], n2[0], n2[1]));
        barrive(5, 256);
      } else {
        bsync(5, 256);
        const uint4 v = lds128(la + 512);
        r2[0] = v.x; r2[1] = v.y; n2[0] = v.z; n2[1] = v.w;
      }
      u32 xn[5][4];
#pragma unroll
      for (int i = 0; i < 20; i++) xn[i >> 2][i & 3] = opaque(hmul2(hadd2(x[i >> 2][i & 3], n2[i & 1]), r2[i & 1]));
      PROFD(elect, 25 + wg, r2[0]);
#pragma unroll 1
      for (u32 ph = 0;; ph++) {
        u32 T[5][4], m = 1, bad = 0;
        mbar_wait(bar(B_YF + 2), ph & 1);
        PROF(elect && wg == 0 && ph == 0, 88);
#pragma unroll
        for (int j = 0; j < 5; j++) {
          u32 A[2], B[2], G[2];
          lds64(B, ma + j * 256); lds64(A, ma + j * 256 + 1280); lds64(G, ma + j * 256 + 2560); lds64(S[j], ma + j * 256 + 3840); lds64(C[j], ma + j * 256 + 5120);
#pragma unroll
          for (int i = 0; i < 2; i++) {
            m = min(min(min(m, A[i]), min(B[i], G[i])), min(S[j][i], C[j][i]));
            A[i] = hmul2(G[i], hadd2(A[i], ONE2)); B[i] = hmul2(G[i], B[i]); C[j][i] = hadd2(C[j][i], ONE2);
          }
#pragma unroll
          for (int i = 0; i < 4; i++) T[j][i] = hfma2(xn[j][i], A[i >> 1], B[i >> 1]);
        }
        clear();
#pragma unroll
        for (int j = 0; j < 5; j++) {
          u32 y[4];
          if (j == YG) PROFD(elect && ph == 0, 27 + wg, __float_as_uint(c[2][0]));
          if (j == 0 || j == YG) mbar_wait(bar(B_YF + (j > 0)), ph & 1);
          if (j == YG) tile_post(p.s->ctr + 32 + 32 * rt + cq, ts, ep, tid == 0);
          if (j == 0 || j == YG) PROF(elect && wg == 0 && ph == 0, j ? 92 : 89);
          ldsm4t(y, ya + j * 4096);
          bad |= (y[0] ^ par) | (y[2] ^ par);
#pragma unroll
          for (int i = 0; i < 4; i++) x1[j][i] = hfma2(y[i], T[j][i], x[j][i]);
          row_stats(c, x1[j]);
        }
        ln_post(c, la + 1024 + warp * 128, lane);
        PROFV(elect, 96, 100 * ph + 100);
        if (__all_sync(0xffffffffu, bsync_and(7, 256, m != 0 && (g != 0 || (bad & 0x10001) == 0)))) break;
        trap_if_gt(ph, 1 << 16);
        RST(__any_sync(0xffffffffu, m == 0) ? 1 : __any_sync(0xffffffffu, g == 0 && (bad & 0x10001)) ? 2 : 0);
        if (warp == 0) { fetch_y(tm, 0, YG, role); fetch_y(tm, YG, 5, role); e_xload(sb + M_MOD, p.s->mod, 6400, bar(B_YF + 2)); }
      }
      mbar_arrive_if(bar(B_HD), lane == 0);
      const u32 th = clock();
      ln_params<8>(la + 1024, r2, n2);
      PROFD(elect, 29 + wg, r2[0]);
      const u32 m0 = (lane & 7) == 2 * cq, m1 = (lane & 7) == 2 * cq + 1;
#pragma unroll
      for (int j = 0; j < 5; j++) {
#pragma unroll
        for (int i = 0; i < 4; i++) {
          const u32 hv = tagw(hfma2(hfma2(x1[j][i], r2[i & 1], n2[i & 1]), C[j][i >> 1], S[j][i >> 1]), (i & 1) ? m1 : m0, par);
          if (j < NH) stg32(hp + (16 * j + (i >> 1)) * 256 + (i & 1) * 32, hv); else zp[4 * j + i] = hv;
        }
        if (j < NH - 1) { until(th, G_S0 + j * G_S); __syncwarp(); }
      }
      PK(elect, 31 + wg);
    }
    const int vg = wg ^ SWAPWG;
    float z[64];
    u32* z2p = (u32*)p.s->z2 + (role * 8 + 2 * w) * 27 * 32 + lane;
#pragma unroll 1
    for (int pass = 0; pass < 2; pass++) {
      if (vg == 0) g1_pass<128>(z, zp, x1[0], pass, t128, z2p, hp, ep);
      else g1_pass<88>(z, zp, x1[0], pass, t128, z2p, hp, ep);
      float st[4] = {0.f, 0.f, 0.f, 0.f};
      auto act = [&](int n0, int n1) {
#pragma unroll
        for (int i = 2 * n0; i < 2 * n1; i++) {
          const float u0 = gelu2(z[2 * i]), u1 = gelu2(z[2 * i + 1]);
          zp[i] = pack2(u0, u1);
          st[2 * (i & 1)] += u0 + u1; st[2 * (i & 1) + 1] = fmaf(u1, u1, fmaf(u0, u0, st[2 * (i & 1) + 1]));
        }
      };
      act(0, 11);
      if (vg == 0) act(11, 16);
      if (pass == 0) {
        const bool up = t & 2;
        float a = (up ? st[2] : st[0]) + shx(up ? st[0] : st[2], 2), q = (up ? st[3] : st[1]) + shx(up ? st[1] : st[3], 2);
        a += shx(a, 1); q += shx(q, 1);
        if (!(t & 1))
          asm volatile("st.relaxed.gpu.global.v2.b32 [%0], {%1,%2};" ::"l"(p.s->stz + (role * 64 + 16 * w + g + 4 * t) * 2 + vg), "f"(a), "r"(prmt(__float_as_uint(q), ep + 1, 0x3214)) : "memory");
        __syncwarp();
        mbar_arrive_if(bar(B_ZP), lane == 0);
      }
      PROFD(elect, 113 + 2 * pass + vg, zp[21]);
    }
    const u32 bs0 = lds32(sb + M_BS + (16 * w + g) * 4), bs1 = lds32(sb + M_BS + (16 * w + g + 8) * 4);
    if (vg == 0) g2_pass<128>(z, elect); else g2_pass<88>(z, elect);
    PROFD(elect, 45 + vg, __float_as_uint(z[0]));
    {
      u32* Pp = (u32*)p.s->P + ((role * 27 + 16 * vg) * 8 + 2 * w) * 32 + lane;
      const u32 m0 = (lane & 7) == 2 * w, m1 = (lane & 7) == 2 * w + 1;
      auto put = [&](int n) { stg32(Pp + n * 256, zp[2 * n]); stg32(Pp + n * 256 + 32, zp[2 * n + 1]); };
      auto gate = [&](int n0, int n1) {
#pragma unroll
        for (int n = n0; n < n1; n++) {
          zp[2 * n] = tagw(hmul2(zp[2 * n], hfma2(pack2(z[4 * n], z[4 * n + 1]), 0x3f003f00u, bs0)), m0, ~ep);
          zp[2 * n + 1] = tagw(hmul2(zp[2 * n + 1], hfma2(pack2(z[4 * n + 2], z[4 * n + 3]), 0x3f003f00u, bs1)), m1, ~ep);
          if (n < NPE) put(n);
        }
      };
      gate(0, 11);
      if (vg == 0) {
        mbar_arrive_if(bar(B_PD), lane == 0);
        gate(11, 16);
#pragma unroll
        for (int n = 0; n < 16; n += 2) stsm4(sb + (((lane >> 4) + n) * 8 + 2 * w) * 128 + (lane & 15) * 16, zp + 2 * n);
        fence_async_smem();
        barrive(5, 256);
      }
#pragma unroll
      for (int n = NPE; n < 11; n++) put(n);
      if (vg == 0) {
#pragma unroll
        for (int n = 11; n < 16; n++) put(n);
      }
    }
    if (vg) {
      float o[80];
      u32 res[60], all = 0;
      PK(elect, 120);
      mbar_wait(bar(B_RES), 0);
      const u32 ra = sb + (t * 8 + 2 * w) * 128 + (g ^ (2 * t)) * 16;
      auto get = [&](int e0, int e1) {
#pragma unroll
        for (int e = e0; e < e1; e++) lds128(res + 4 * e, e < 10 ? ra + (e < 6 ? RES + (e >> 1) * 4096 : e < 8 ? M_MOD : RES2) + (e & 1) * 128 : sb + RES2 + 4096 + (e - 10) * 64 + t * 16);
      };
      get(0, NR0);
      mbar_wait(bar(B_WF), 0); mbar_wait(bar(B_WF + 1), 0);
      bsync(4, 256);
      PROF(elect, 50);
      wg_fence();
#pragma unroll
      for (int q = 0; q < 5; q++) { wgmma_rs_160(o, zp + 4 * q, desc_join(desc_lo(sb + BT + q * 5120, 2560), 8u), q); if (q == 2 || q == 4) wg_commit(); }
      stsm2(sb + XR + 2 * w * 128 + (lane & 15) * 16, zp[20], zp[21]);
      fence_async_smem();
      get(NR0, NR1);
      bsync(5, 256);
      PK(elect, 48);
      wg_fence();
      wgmma_ss_160(o, desc_join(desc_lo(sb, 1024), 8u), desc_join(desc_lo(sb + BT + 5 * 5120, 2560), 8u), 1);
      wg_commit();
      wg_wait<1>();
      mbar_arrive_if(bar(B_WE), elect);
      u32 la = desc_lo(sb + 2048, 1024), lb = desc_lo(sb + BT + 2 * WOST, 2560), bf = bar(B_WF + 2), bprev = bar(B_WE + 1), par = 0, bv = bar(B_PV - 1), kb = 4;
#pragma unroll 1
      do {
        bool go;
        if (kb == 16) {
          get(NR1, 15);
#pragma unroll
          for (int e = 0; e < 15; e++) all ^= res[4 * e];
          consume(all);
          mbar_arrive_if(bar(B_PD), lane == 0);
        }
        if (kb >= 16) mbar_wait(bv, 0);
        mbar_wait(bf, par);
        PROF(elect && kb == 16, 49);
#pragma unroll 1
        do {
          wg_fence();
          wgmma_ss_160(o, desc_join(la, 8u), desc_join(lb, 8u), 1);
          la += kb == 16 ? (XR >> 4) - 7 * 128 : 128;
          const u32 bcur = bf + 8 * (B_WE - B_WF);
          const bool wrap = kb & 0x2040;
          kb *= 2; par ^= wrap; bf += wrap ? -48 : 8; bv += (kb & 0x9550) ? 8 : 0;
          const bool t0 = mbar_test(bf, par), t1 = mbar_test(bv, 0);
          wgmma_ss_160(o, desc_join(la, 8u), desc_join(lb + 320, 8u), 1);
          wgmma_ss_160(o, desc_join(la + 128, 8u), desc_join(lb + 640, 8u), 1);
          wg_commit();
          go = __all_sync(0xffffffffu, t0 & (t1 | (kb < 16)) & !(kb & 0x40010));
          la += 256; lb += wrap ? -6 * (int)(WOST >> 4) : (int)(WOST >> 4);
          wg_wait<1>();
          mbar_arrive_if(bprev, elect);
          bprev = bcur;
          PROFG(elect, 33 - __clz(kb));
        } while (go);
      } while (kb != 0x40000);
      wg_wait<0>();
      PROFD(elect, 52, __float_as_uint(o[0]));
      u16* op = p.out + (rt * 64 + 16 * w + g) * 640 + 160 * cq + 8 * t;
#pragma unroll
      for (int i = 0; i < 10; i++) {
        const int be = i >> 1, h = i & 1;
        u32 r[4];
#pragma unroll
        for (int e = 0; e < 4; e++) r[e] = hfma2(pack2(o[16 * be + 4 * e + 2 * h], o[16 * be + 4 * e + 2 * h + 1]), res[40 + 4 * be + e], res[4 * i + e]);
        stg128(op + h * 8 * 640 + 32 * be, make_uint4(r[0], r[1], r[2], r[3]));
      }
      PK(elect, 53);
    }
  } else {
    asm volatile("setmaxnreg.dec.sync.aligned.u32 56;");
    const int hw = warp - 8;
    if (hw == 0) {
      {
        const int n = lane < 15 ? (int)(ORDER >> (4 * lane)) & 15 : lane, j = n < 15 ? (n * 11) >> 5 : n < 20 ? n - 15 : n - 20, ty = n < 15 ? n - 3 * j : n < 20 ? 3 : 4;
        const int c0 = ty < 2 ? 128 * j + 64 * (role & 1) : ty == 2 ? 0 : ty == 3 ? 32 * role : 64 * j;
        const int c1 = ty < 2 ? 32 * (role >> 1) - 3 + 3 * ty : ty == 2 ? 1024 * j + 8 * role : ty == 3 ? 128 * j : 16 * role;
        const u32 dst = sb + (ty < 2 ? j * KVP + ty * VO : ty == 2 ? kslot(j) : ty == 3 ? WM + j * 8192 : QS + j * 2048);
        const u32 br = bar(ty < 2 ? B_KV + j : ty == 2 ? B_SS + j : ty == 3 ? B_WM + j : B_Q), bytes = ty == 0 ? VO : ty < 3 ? 4096 : ty == 3 ? 8192 : 2048;
        int due = T_0 + 3 * T_G;
#pragma unroll 1
        for (int i = 3; i < 30; i++) {
          until(t_start, due);
          if (lane == i) xtma2d(dst, &tm.k + ty, br, c0, c1, bytes);
          PROF(lane == i && (i < 4 || i == 29), 96 + lane);
          due += i < 15 ? T_G + (i == 14 ? T_X : 0) : i < 20 ? 2 * T_G2 : T_G2 / 2;
          __syncwarp();
        }
      }
      const u32 ep = ld_rlx32(p.s->ctr);
      {
        ctr_poll(p.s->ctr, I_WS, ep, 4);
        PROF(lane == 0, 33);
        const u16* src = p.s->ws + cq * 56320;
#pragma unroll 1
        for (int r = 0; r < 4; r++) {
          if (r == 2) { mbar_wait(bar(B_WS1), 0); if (WL < 5) mbar_wait(bar(B_EMPTY + WL), 0); else mbar_wait(bar(B_FULL + 4), 1); src += 3 * 56320; }
#pragma unroll 1
          for (int s = 0; s < 5; s++, src += 5632) {
            if (r == 0) until(t_start, T_W + s * G_W);
            w_g1(bar(B_EMPTY) + 8 * s, r & 1, bar(B_FULL) + 8 * s, sb + s * BT, &tm.win, (r < 2 ? 896 : 0) + 192 * cq, 64 * s + 320 * (r & 1), src);
            PROF(lane == 0 && r == 0, 74 + s); PROFG(lane == 0 && r == 2 * PG1 + 1, 21 + s);
          }
        }
      }
      e_expect(bar(B_FULL + 5), BT + 8192);
      e_tma2d(sb + AR, &tm.wsp, bar(B_FULL + 5), 0, 64 * rt);
      mbar_wait(bar(B_Z2D), 0);
      const int tz = lds32(sb + M_TZ);
      fence_gpu();
      ctr_arrive(p.s->ctr, I_Z2, ep, lane);
      PROF(lane == 0, 36);
      until(t_start, tz + D_Z);
      PROF(lane == 0, 35);
      {
        const u16* src = p.s->z2 + cq * (BT / 2);
        u32 par = 0;
#pragma unroll 1
        for (int c0 = 0;; par ^= 1) {
#pragma unroll
          for (int e = 0; e < 6; e++, c0 += 64, src += 2 * BT) {
            const int s = (e + 5) % 6;
            if (e == 2 && c0 == 2048) break;
            if (e == 0 && c0 == 0) e_load(sb + s * BT, src, BT, bar(B_FULL + s)); else
            w_g2(bar(B_EMPTY + s), e ? par : par ^ 1, bar(B_FULL + s), sb + s * BT, src, sb + AR + e * 8192, &tm.wsp, c0, 64 * rt);
            if (e == NV - 1 && c0 < 384) { ctr_poll(p.s->ctr, I_Z2, ep, 128); PROF(lane == 0, 37); }
          }
          if (c0 == 2048) break;
          if (c0 == 1152) {
            e_expect(bar(B_RES), 20800);
            e_load(sb + M_MOD, p.s->x1 + role * 10240 + 6144, 4096, bar(B_RES));
            e_load(sb + RES2, p.s->x1 + role * 10240 + 8192, 4096, bar(B_RES));
            e_load(sb + RES2 + 4096, p.s->mod + 3200 + 160 * cq, 320, bar(B_RES));
          }
        }
      }
      if (role == 0 && lane < 9) p.s->ctr[lane ? 15 - 8 * (ep & 1) + lane : 0] = lane ? 0 : ep + 1;
      if (role < 100 && lane < 16) stg32((u32*)p.s->mod + role * 16 + lane, 0);
      mbar_wait(bar(B_WO), 0);
      {
        const u16* src = p.s->wo + cq * 18 * (WOST / 2);
#pragma unroll 1
        for (int i = 0; i < 7; i++, src += WOST / 2) {
          w_load<WOST>(bar(B_EMPTY + 1) + 8 * ((i + 1) >> 1), 1, bar(B_WF) + 8 * i, sb + BT + i * WOST, src);
          stamp_post(p.s->ctr, ep, S_P, t_start, lane + i);
          if (i == 2) e_load(sb + RES, p.s->x1 + role * 10240, 12288, bar(B_RES));
        }
        int due = stamp_wait(p.s->ctr, ep, S_P) + T_R;
#pragma unroll 1
        for (int r = 0; r < 2; r++) {
#pragma unroll 1
          for (int i = 0; i < 7 - 3 * r; i++, src += WOST / 2, due += G_R) { until(t_start, due); w_load<WOST>(bar(B_WE) + 8 * i, r, bar(B_WF) + 8 * i, sb + BT + i * WOST, src); }
        }
      }
    } else {
      u32 rph = 0, ep = ld_rlx32(p.s->ctr);
      if (hw == 1) {
        tile_wait(p.s->ctr + 32 + 32 * rt, ep - 1);
#pragma unroll 1
        for (int j = 0; j < 5; j++) {
          const int due = j ? T_U1 + j * T_UP : T_U0;
          until(t_start, due - D_U);
          if (!__all_sync(0xffffffffu, mbar_test(bar(B_KV + j), 0))) { mbar_wait(bar(B_KV + j), 0); until(clock(), D_U); }
          until(t_start, due);
          PROF(lane == 0, j ? 53 + j : 38);
          const u16* src = p.s->u + (128 * j + role) * 2048;
          e_xload(sb + US + j * UP, src, 4096, bar(B_RF));
          rph ^= 1;
          const int n = validate<4>(bar(B_RF), rph ^ 1, sb + US + j * UP, lane * 32, ep, bar(B_UV + j), src, bar(B_RF), rph);
          if (n) RST(j ? j > 1 ? 3 + j : 3 : 10);
          PROF(lane == 0, 64 + j); PROFV(lane == 0, 69 + j, 100 * n + 100);
        }
        mbar_wait(bar(B_EMPTY + 3), 0);
        const int ty = stamp_wait(p.s->ctr, ep, S_Y);
        if (YG == 4) until(t_start, ty + D_Y3);
        fetch_y(tm, 0, YG, role);
        PROF(lane == 0, 58);
        until(t_start, ty + D_Y);
        fetch_y(tm, YG, 5, role);
        PROF(lane == 0, 59);
        {
          mbar_wait(bar(B_YF + 1), 0);
          const u32 t0 = t_start + max(tile_wait(p.s->ctr + 32 + 32 * rt, ep), ty + D_Y + D_HG);
          mbar_wait(bar(B_HD), 0);
#pragma unroll 1
          for (int j = 0; j < 5; j++) {
            until(t0, D_H + j * G_H);
            e_xload(sb + XR + j * 16384, p.s->h2 + (rt * 5 + j) * 8192, 16384, bar(B_SS + j));
            PROF(lane == 0 && j == 0, 60);
          }
        }
        const u32 t0 = clock();
#pragma unroll 1
        for (int i = 0; i < 16; i++) { until(t0, i * T_PF); e_prefetch(p.wsp + (role * 16 + i) * 2048, 4096); }
      } else {
        const int hi = hw - 2;
        const u32 ts = __shfl_sync(0xffffffffu, t_start, 0);
        const u32 d0 = __ldg(p.ssmD + 128 * min(lane, 4) + role);
        {
          const int ht = tid - 320, g = lane >> 2, t = lane & 3;
          const u32 bs = __ldg(p.bsp + rt * 64 + ht);
          u32 cv[5];
#pragma unroll
          for (int i = 0; i < 5; i++) cv[i] = __ldg((const u32*)p.c + ht + 64 * i);
#pragma unroll 1
          for (int i = 0; i < 5; i++) {
            const float a = bflo(cv[0]), b = bfhi(cv[0]);
            const u32 v = pack2(__fdividef(a, 1.f + __expf(-a)), __fdividef(b, 1.f + __expf(-b))), ad = sb + M_SC + i * 256 + hi * 128 + t * 32 + g * 2;
            sts16(ad, v); sts16(ad + 16, v >> 16);
#pragma unroll
            for (int j = 0; j < 4; j++) cv[j] = cv[j + 1];
          }
          sts32(sb + M_D + 4 * min(lane, 4), d0);
          sts32(sb + M_BS + 4 * ht, hmul2(bs * 0x10001u, 0x3f003f00u));
          __syncwarp();
        }
        ep = __shfl_sync(0xffffffffu, ep, 0);
        mbar_wait(bar(B_KV), 0);
#pragma unroll 1
        for (int j = 2; j < 5; j++) {
          const int lane = lane_now(), ht = 32 * hi + lane;
          if (H4 && j == 4) {
            mbar_wait(bar(B_KV + 4), 0);
            PROF(ht == 0, 93);
            phase_a<2>(p, 4, hi, role, lane, (opaque(ep) & 1) - 1);
            __syncwarp();
            e_arrive(bar(B_EMPTY + 1));
            PROF(ht == 0, 79);
          }
          mbar_wait(bar(B_SS + j), 0);
          shift_copy<4, 1024>(sb + kslot(j) + hi * 512 + lane_now() * 16, lds32(sb + M_D + 4 * j), hi + lane_now() == 0);
          __syncwarp();
          e_arrive(bar(B_KB + j - 2));
          PROF(ht == 0, 78 + j);
        }
        const int lane = lane_now(), ht = 32 * hi + lane, g = lane >> 2;
        {
          float acc[8] = {0.f, 0.f, 0.f, 0.f, 0.f, 0.f, 0.f, 0.f};
#pragma unroll 1
          for (int j = 0; j < 5; j++) {
            u32 cv[4], wv[8][4];
            mbar_wait(bar(B_WM + j), 0);
            if (j == 4) stamp_post(p.s->ctr, ep, S_MOD, ts, ht);
            PROF(ht == 0, 83 + j);
            lds128(cv, sb + M_SC + j * 256 + hi * 128 + g * 16);
#pragma unroll
            for (int i = 0; i < 8; i++) lds128(wv[i], sb + WM + j * 8192 + hi * 4096 + i * 512 + lane * 16);
#pragma unroll
            for (int i = 0; i < 8; i++) {
              const float c = (i & 1) ? bfhi(cv[i >> 1]) : bflo(cv[i >> 1]);
#pragma unroll
              for (int e = 0; e < 4; e++) { acc[2 * e] = fmaf(bflo(wv[i][e]), c, acc[2 * e]); acc[2 * e + 1] = fmaf(bfhi(wv[i][e]), c, acc[2 * e + 1]); }
            }
          }
          const u32 pa = sb + WM + hi * 4096;
          sts128(pa + lane * 32, make_uint4(__float_as_uint(acc[0]), __float_as_uint(acc[1]), __float_as_uint(acc[2]), __float_as_uint(acc[3])));
          sts128(pa + lane * 32 + 16, make_uint4(__float_as_uint(acc[4]), __float_as_uint(acc[5]), __float_as_uint(acc[6]), __float_as_uint(acc[7])));
          bsync(6, 64);
          if (ht < 16) {
            float s[4] = {0.f, 0.f, 0.f, 0.f};
            const u32 ra = sb + WM + (role < 100 ? (ht & 3) * 32 + (ht >> 2) * 8 : ht * 8);
#pragma unroll
            for (int i = 0; i < 16; i++) { u32 v[2]; lds64(v, ra + (i >> 3) * 4096 + (i & 7) * 128); s[i & 2] += __uint_as_float(v[0]); s[(i & 2) + 1] += __uint_as_float(v[1]); }
            stg32((u32*)p.s->mod + role * 16 + ht, nz(pack2(s[0] + s[2], s[1] + s[3])));
          }
          __syncwarp();
          mbar_arrive_if(bar(B_EMPTY + 3), ht == 0);
          PROF(ht == 0, 39);
        }
        if (hi == 0) {
          until(ts, stamp_wait(p.s->ctr, ep, S_MOD) + D_M);
          PROF(lane == 0, 95);
          e_xload(sb + M_MOD, p.s->mod, 6400, bar(B_YF + 2));
        }
#pragma unroll 1
        for (int i = 0; i < 5; i++) {
          const int n = validate<8>(bar(B_SS + i), 1, sb + XR + i * 16384 + hi * 8192, lane * 32 + g * 4, ep, bar(B_VAL + i),
                                    p.s->h2 + (rt * 5 + i) * 8192 + hi * 4096, bar(B_RF + hw - 1), rph);
          if (i == 0) { e_arrive(bar(B_EMPTY + 4)); stamp_post(p.s->ctr, ep, S_Z, ts, ht); }
          if (i == 1 && hi == 0) { ctr_poll(p.s->ctr, I_WS + 1, ep, 4); e_arrive(bar(B_WS1)); PROF(lane == 0, 34); }
          PROF(ht == 0 && (i == 0 || i == 4), i ? 63 : 62); PROFV(ht == 0 && n, 97, 100 * i + 100);
        }
        if (hi) sts32(sb + M_TZ, stamp_wait(p.s->ctr, ep, S_Z));
        {
          mbar_wait(bar(B_ZP), 0);
          until(clock(), T_ZS);
          float s, q;
          int n = 0;
#pragma unroll 1
          while (true) {
            uint4 v[4];
            u32 bad = 0;
#pragma unroll
            for (int i = 0; i < 4; i++) v[i] = ld_rlx128(p.s->stz + ((rt * 4 + i) * 64 + ht) * 2);
            s = 0.f; q = 0.f;
#pragma unroll
            for (int i = 0; i < 4; i++) {
              bad |= (v[i].y ^ (ep + 1)) | (v[i].w ^ (ep + 1));
              s += __uint_as_float(v[i].x) + __uint_as_float(v[i].z); q += __uint_as_float(v[i].y) + __uint_as_float(v[i].w);
            }
            if (__all_sync(0xffffffffu, (bad & 255) == 0)) break;
            trap_if_gt(++n, 1 << 20);
          }
          const float mu = s * (1.f / 864.f), rs = rsq(fmaxf(q * (1.f / 864.f) - mu * mu, 0.f) + 4e-5f);
          sts32(sb + M_ZS + ht * 4, pack2(rs, -mu * bfhi(pack2(rs, rs))));
          __syncwarp();
          e_arrive(bar(B_ZS));
        }
      }
      const u32 off = lane_now() * 33 & ~3;
#pragma unroll 1
      for (int i = 0, s = 5; i < NV; i++) {
        const int n = validate<9>(bar(B_FULL) + 8 * s, 0, sb + s * BT + (hw - 1) * 9216, off, ep, bar(B_ZV) + 8 * i,
                                  p.s->z2 + (i * 4 + cq) * (BT / 2) + (hw - 1) * 4608, bar(B_RF + hw - 1), rph);
        PROFV(lane == 0 && n, 118, 100 * i + 100);
        s = s == 5 ? 0 : s + 1;
      }
      if (hw == 1) { until(clock(), T_WO); ctr_poll(p.s->ctr, I_WO, ep, 4); e_arrive(bar(B_WO)); PROF(lane == 0, 94); }
      mbar_wait(bar(B_WF), 0);
      const int tp = stamp_wait(p.s->ctr, ep, S_P);
      mbar_wait(bar(B_EMPTY + 5), 1);
      const u16* src = p.s->P + (rt * 4 + ((cq + hw) & 3)) * (BT / 2);
      const u32 due = t_start + tp + ((cq + hw) & 3) * G_P, rb = bar(B_RF + hw - 1), da = sb + XR + 1024 + (hw - 1) * 11264, db = sb + XR + 34816 + (hw - 1) * 16384;
      until(due, T_P);
      e_xload(da, src + 8192, 11264, rb);
      PROF(hw == 1 && lane == 0, 100);
      rph ^= 1;
      validate<11>(rb, rph ^ 1, da, off, ep, bar(B_PV + hw - 1), src + 8192, rb, rph);
      PROF(hw == 1 && lane == 0, 101);
      until(due, T_P2);
      w_load<16384>(bar(B_PD), 0, rb, db, src);
      PROF(hw == 1 && lane == 0, 102);
      rph ^= 1;
      validate<16>(rb, rph ^ 1, db, off, ep, bar(B_PV + hw + 2), src, rb, rph);
      PROF(hw == 1 && lane == 0, 103);
    }
  }
}

typedef CUresult (*EncodeFn)(CUtensorMap*, CUtensorMapDataType, cuuint32_t, void*, const cuuint64_t*, const cuuint64_t*, const cuuint32_t*,
                             const cuuint32_t*, CUtensorMapInterleave, CUtensorMapSwizzle, CUtensorMapL2promotion, CUtensorMapFloatOOBfill);

extern "C" void kernel_launch(void* const* d_in, const int* in_sizes, int n_in, void* d_out, int out_size) {
  static EncodeFn enc = nullptr;
  if (!enc) {
    void* fn = nullptr; cudaDriverEntryPointQueryResult st;
    cudaGetDriverEntryPoint("cuTensorMapEncodeTiled", &fn, cudaEnableDefault, &st);
    enc = (EncodeFn)fn;
    cudaFuncSetAttribute(mega_kernel, cudaFuncAttributeMaxDynamicSharedMemorySize, SMEM_BYTES);
  }
  Params p;
  p.shk = (const u16*)d_in[3]; p.ssmD = (const u16*)d_in[5];
  p.wsp = (const u16*)d_in[8]; p.bsp = (const u16*)d_in[9]; p.c = (const u16*)d_in[11];
  p.out = (u16*)d_out;
  cudaGetSymbolAddress((void**)&p.s, g_s);
  auto mk = [&](void* base, int rank, cuuint64_t d0, cuuint64_t d1, cuuint32_t b0, cuuint32_t b1, CUtensorMapSwizzle sw) {
    CUtensorMap m;
    cuuint64_t gd[3] = {d0, d1, 2}, gs[2] = {d0 * 2, 128};
    cuuint32_t bd[3] = {b0, b1, 2}, es[3] = {1, 1, 1};
    enc(&m, CU_TENSOR_MAP_DATA_TYPE_BFLOAT16, rank, base, gd, gs, bd, es, CU_TENSOR_MAP_INTERLEAVE_NONE, sw, (CUtensorMapL2promotion)PROMO,
        CU_TENSOR_MAP_FLOAT_OOB_FILL_NONE);
    return m;
  };
  Maps tm;
  tm.k = mk(d_in[1], 2, 640, 2048, 64, 35, CU_TENSOR_MAP_SWIZZLE_NONE);
  tm.v = mk(d_in[2], 2, 640, 2048, 64, 32, CU_TENSOR_MAP_SWIZZLE_NONE);
  tm.ssm = mk(d_in[4], 2, 256, 5120, 256, 8, CU_TENSOR_MAP_SWIZZLE_NONE);
  tm.wmod = mk(d_in[12], 2, 3840, 640, 32, 128, CU_TENSOR_MAP_SWIZZLE_NONE);
  tm.q = mk(d_in[0], 2, 640, 2048, 64, 16, CU_TENSOR_MAP_SWIZZLE_128B);
  tm.win = mk(d_in[7], 3, 1728, 640, 64, 64, CU_TENSOR_MAP_SWIZZLE_128B);
  tm.wsp = mk(d_in[8], 2, 2048, 2048, 64, 64, CU_TENSOR_MAP_SWIZZLE_128B);
  tm.y = mk(p.s->y, 2, 64, 20480, 16, 128, CU_TENSOR_MAP_SWIZZLE_32B);
  tm.win32 = mk(d_in[7], 2, 1728, 640, 32, 128, CU_TENSOR_MAP_SWIZZLE_64B);
  tm.wout = mk(d_in[10], 2, 640, 864, 160, 24, CU_TENSOR_MAP_SWIZZLE_NONE);
  mega_kernel<<<132, 384, SMEM_BYTES>>>(p, tm);
}
```
